```python
import torch

def _softmax(x, axis=-1):
    return torch.softmax(x, dim=axis)
def _gelu(x):
    return torch.nn.functional.gelu(x, approximate="tanh")
def _silu(x):
    return torch.nn.functional.silu(x)
def _sigmoid(x):
    return torch.sigmoid(x)
def _layernorm(x, axis=-1, eps=1e-5):
    m = x.mean(dim=axis, keepdim=True)
    v = x.var(dim=axis, keepdim=True, unbiased=False)
    return (x - m) / torch.sqrt(v + eps)
def _scatter_add(tgt, idx, src, axis=0):
    return tgt.clone().index_add_(axis, idx, src)
def _segment_sum(src, seg, n):
    out = torch.zeros((n,) + src.shape[1:], dtype=src.dtype)
    return out.index_add_(0, seg, src)
def _pad(x, pw):
    flat = tuple(v for pair in reversed(pw) for v in pair)
    return torch.nn.functional.pad(x, flat)

kernel_name = 'recurrent_scan__mha_block_cached__swiglu_ffn__decode'

def setup_inputs():

    _w = (lambda a: (lambda t: t.to(torch.bfloat16) if t.is_floating_point() else t)(torch.as_tensor(a)))
    def _A_setup():
        B, Sq, D = 1, 1, 640
        H, Sk, Dh = 32, 4096, 192
        return {
            "x": _w((lambda *s: torch.randn(*s, dtype=torch.bfloat16) * 0.05)(B, Sq, D)),
            "k_cache": _w((lambda *s: torch.randn(*s, dtype=torch.bfloat16) * 1.6)(B, H, Sk, Dh)),
            "v_cache": _w((lambda *s: torch.randn(*s, dtype=torch.bfloat16) * 0.2)(B, H, Sk, Dh)),
            "wq": _w((lambda *s: torch.randn(*s, dtype=torch.bfloat16) * 1.6)(D, H * Dh) * (D ** -0.5)),
            "wo": _w((lambda *s: torch.randn(*s, dtype=torch.bfloat16) * 0.2)(H * Dh, D) * ((H * Dh) ** -0.5)),
        }
    _A_in = _A_setup()

    def _B_setup():
        B, S, D, F = 1, 1, 640, 1536
        return {
            "x": _w((lambda *s: torch.randn(*s, dtype=torch.bfloat16) * 0.05)(B, S, D)),
            "w_gate": _w((lambda *s: torch.randn(*s, dtype=torch.bfloat16) * 0.1)(D, F)),
            "w_up": _w((lambda *s: torch.randn(*s, dtype=torch.bfloat16) * 0.1)(D, F)),
            "w_down": _w((lambda *s: torch.randn(*s, dtype=torch.bfloat16) * 0.1)(F, D)),
        }
    _B_in = _B_setup()

    return {
        "A_x": _A_in["x"],
        "A_k_cache": _A_in["k_cache"],
        "A_v_cache": _A_in["v_cache"],
        "A_wq": _A_in["wq"],
        "A_wo": _A_in["wo"],
        "B_x": _B_in["x"],
        "B_w_gate": _B_in["w_gate"],
        "B_w_up": _B_in["w_up"],
        "B_w_down": _B_in["w_down"],
    }

def reference(A_x, A_k_cache, A_v_cache, A_wq, A_wo, B_x, B_w_gate, B_w_up, B_w_down):
    def _A_ref(x, k_cache, v_cache, wq, wo):
        B, Sq, D = x.shape
        H, Dh = 32, 192
        q = (lambda x, *d: x.permute(*d))((x @ wq).reshape(B, Sq, H, Dh), 0, 2, 1, 3)
        scores = torch.einsum("bhqd,bhkd->bhqk", q, k_cache) * (Dh ** -0.5)
        p = _softmax(scores, axis=-1)
        o = torch.einsum("bhqk,bhkd->bhqd", p, v_cache)
        return (lambda x, *d: x.permute(*d))(o, 0, 2, 1, 3).reshape(B, Sq, H * Dh) @ wo

    def _B_ref(x, w_gate, w_up, w_down):
        g = _silu(x @ w_gate)
        u = x @ w_up
        return (g * u) @ w_down

    x = A_x
    xn = _layernorm(x, axis=-1)
    s = _A_ref(xn, A_k_cache, A_v_cache, A_wq, A_wo)
    g = _silu(_B_ref(xn, B_w_gate, B_w_up, B_w_down))
    return x + s * g
```

```cpp
#include <cuda.h>
#include <cuda_runtime.h>
#include <cuda_bf16.h>
#include <stdint.h>

namespace {

constexpr int D = 640, H = 32, DH = 192, SK = 4096, F = 1536;
constexpr int PARTS = 4, NCTA = H * PARTS;
constexpr int KSLOTS = 8, KSLOT_BYTES = 24576;
constexpr int VSLOTS = 6, VSLOT_BYTES = 32768;
constexpr int NKT = 16, NVT = 16;
constexpr int POS_K = 4, NPOS1 = POS_K + NKT;
constexpr int VSLOT0 = 3;
constexpr int CW = 64;
constexpr int ROW_BYTES = D * 2;
constexpr int BLK16 = 16 * ROW_BYTES;
constexpr int NFFN = F / CW;
constexpr int NS = H * 3;
constexpr int P1_ROWS = D / PARTS;
constexpr int WQ_BOX = 32 * DH * 2;
constexpr int NUNIT = D / 8;
constexpr int DCOLS = 32, DROWS = 192;
constexpr int DBOX = DCOLS * DROWS * 2;
constexpr int HEAD_D0 = H - D / DCOLS;
constexpr int NTHREADS = 352, NB7 = 64;
constexpr int SPIN_LIMIT = 1 << 20;
constexpr uint32_t WAIT_CLOCKS = 1u << 30;

#define DEPTH_START 4
#define DEPTH_MID 6
#define DEPTH_V 4
#define DEPTH_END 4
#define KFIRST 1
#define DEPTH_F 5
#define PI4 -1
#define PI5 0
#define POS_MID 8
#define SLEAD 1
#define EARLY 2
#define NPRE 1
#define SLEEP_Q 100
#define SLEEP_OUT 0

struct Par { int ka, kb, pa, pb, pc, fa, fb, ds, dm, dv, de, df, pm, so, wa, wb, tp, td; };
#define PAR(n, d) (d)
#define WA 0
#define WB 0
#define TPOLL 37000
#define TDELTA 150
#define KA 1000
#define KB 980
#define PA 17300
#define PB 1100
#define PC 600
#define FA 0
#define FB 0

constexpr int SM_RING = 0;
constexpr int SM_S = KSLOTS * KSLOT_BYTES;
constexpr int SM_X = SM_S + SK * 4;
constexpr int SM_RED = SM_X + 1408;
constexpr int RED_STRIDE = DH * 4;
constexpr int SM_P = SM_RED + 10 * RED_STRIDE;
constexpr int SM_Q = SM_P + 8 * 256;
constexpr int SM_O = SM_Q + DH * 2;
constexpr int SM_MISC = SM_O + CW * 4;
constexpr int SM_BAR = SM_MISC + 64;
constexpr int SM_TS = SM_BAR + 320;
constexpr int SMEM_BYTES = SM_TS;

#define ACC_PAD 272
#define ACC_GRP 16
#define STAG 0
#define PF 1
#define PIN 1
#define TOFF 650
#define XG 0
#define GPOS 15
struct __align__(128) Scratch {
    unsigned epoch[32];
    float xq[NCTA * DH];
    uint32_t xs[H * SK];
    uint32_t xh[F];
    uint32_t xg[D];
    unsigned long long acc[D / ACC_GRP * ACC_PAD];
    float ps[NUNIT * NS * 8];
};
__device__ Scratch g_scratch;

#define TP(i) do {} while (0)
#define TS(i) do {} while (0)
#define TSDUMP(mask) do {} while (0)

__device__ __forceinline__ uint32_t smem_addr(const void* p) { return (uint32_t)__cvta_generic_to_shared(p); }
__device__ __forceinline__ void mbar_init(uint32_t bar, uint32_t cnt) {
    asm volatile("mbarrier.init.shared::cta.b64 [%0], %1;" ::"r"(bar), "r"(cnt) : "memory");
}
__device__ __forceinline__ void mbar_arrive(uint32_t bar) {
    asm volatile("mbarrier.arrive.shared::cta.b64 _, [%0];" ::"r"(bar) : "memory");
}
__device__ __forceinline__ bool mbar_try(uint32_t bar, uint32_t parity) {
    uint32_t ok;
    asm volatile("{\n.reg .pred p;\nmbarrier.try_wait.parity.shared::cta.b64 p, [%1], %2;\nselp.u32 %0, 1, 0, p;\n}"
                 : "=r"(ok) : "r"(bar), "r"(parity) : "memory");
    return ok;
}
__device__ __forceinline__ bool mbar_test(uint32_t bar, uint32_t parity) {
    uint32_t ok;
    asm volatile("{\n.reg .pred p;\nmbarrier.test_wait.parity.shared::cta.b64 p, [%1], %2;\nselp.u32 %0, 1, 0, p;\n}"
                 : "=r"(ok) : "r"(bar), "r"(parity) : "memory");
    return ok;
}
__device__ __forceinline__ void mbar_wait(uint32_t bar, uint32_t parity) {
    if (mbar_try(bar, parity)) return;
    const uint32_t t0 = (uint32_t)clock();
#pragma unroll 1
    while (!mbar_try(bar, parity))
        if ((uint32_t)clock() - t0 > WAIT_CLOCKS) __trap();
}
__device__ __forceinline__ void bar_sync(int id, int n) { asm volatile("bar.sync %0, %1;" ::"r"(id), "r"(n) : "memory"); }
__device__ __forceinline__ void ldsm4(uint32_t (&a)[4], uint32_t addr) {
    asm volatile("ldmatrix.sync.aligned.m8n8.x4.shared.b16 {%0,%1,%2,%3}, [%4];"
                 : "=r"(a[0]), "=r"(a[1]), "=r"(a[2]), "=r"(a[3]) : "r"(addr) : "memory");
}
__device__ __forceinline__ void ldsm4t(uint32_t (&a)[4], uint32_t addr) {
    asm volatile("ldmatrix.sync.aligned.m8n8.x4.trans.shared.b16 {%0,%1,%2,%3}, [%4];"
                 : "=r"(a[0]), "=r"(a[1]), "=r"(a[2]), "=r"(a[3]) : "r"(addr) : "memory");
}
__device__ __forceinline__ void mma16816(float (&c)[4], const uint32_t (&a)[4], uint32_t b0, uint32_t b1) {
    asm volatile("mma.sync.aligned.m16n8k16.row.col.f32.bf16.bf16.f32 {%0,%1,%2,%3}, {%4,%5,%6,%7}, {%8,%9}, {%0,%1,%2,%3};"
                 : "+f"(c[0]), "+f"(c[1]), "+f"(c[2]), "+f"(c[3])
                 : "r"(a[0]), "r"(a[1]), "r"(a[2]), "r"(a[3]), "r"(b0), "r"(b1));
}
__device__ __forceinline__ float bf16r(float v) { return __bfloat162float(__float2bfloat16_rn(v)); }
__device__ __forceinline__ uint32_t bf16bits(float v) { return (uint32_t)__bfloat16_as_ushort(__float2bfloat16_rn(v)); }
__device__ __forceinline__ uint32_t pack2(float lo, float hi) {
    uint32_t r;
    asm("cvt.rn.bf16x2.f32 %0, %1, %2;" : "=r"(r) : "f"(hi), "f"(lo));
    return r;
}
__device__ __forceinline__ float silu(float v) { return __fdividef(v, 1.0f + __expf(-v)); }
__device__ __forceinline__ uint32_t tagged(float v, uint32_t tag) { return (__float_as_uint(v) & ~3u) | tag; }
__device__ __forceinline__ void st_rlx(void* p, uint32_t v) {
    asm volatile("st.relaxed.gpu.global.b32 [%0], %1;" ::"l"(p), "r"(v) : "memory");
}
__device__ __forceinline__ void st_rlx4(void* p, uint4 v) {
    asm volatile("st.relaxed.gpu.global.v4.b32 [%0], {%1,%2,%3,%4};" ::"l"(p), "r"(v.x), "r"(v.y), "r"(v.z), "r"(v.w) : "memory");
}
__device__ __forceinline__ uint32_t ld_rlx(const void* p) {
    uint32_t v;
    asm volatile("ld.relaxed.gpu.global.b32 %0, [%1];" : "=r"(v) : "l"(p) : "memory");
    return v;
}
__device__ __forceinline__ uint4 ld_rlx4(const void* p) {
    uint4 v;
    asm volatile("ld.relaxed.gpu.global.v4.b32 {%0,%1,%2,%3}, [%4];" : "=r"(v.x), "=r"(v.y), "=r"(v.z), "=r"(v.w) : "l"(p) : "memory");
    return v;
}
__device__ __forceinline__ float lds_f(uint32_t a) { float v; asm volatile("ld.shared.f32 %0, [%1];" : "=f"(v) : "r"(a) : "memory"); return v; }
__device__ __forceinline__ void sts_f(uint32_t a, float v) { asm volatile("st.shared.f32 [%0], %1;" ::"r"(a), "f"(v) : "memory"); }
__device__ __forceinline__ void sts_u(uint32_t a, uint32_t v) { asm volatile("st.shared.b32 [%0], %1;" ::"r"(a), "r"(v) : "memory"); }
__device__ __forceinline__ uint32_t lds_u(uint32_t a) { uint32_t v; asm volatile("ld.shared.b32 %0, [%1];" : "=r"(v) : "r"(a) : "memory"); return v; }
__device__ __forceinline__ uint4 lds_u4(uint32_t a) {
    uint4 v;
    asm volatile("ld.shared.v4.b32 {%0,%1,%2,%3}, [%4];" : "=r"(v.x), "=r"(v.y), "=r"(v.z), "=r"(v.w) : "r"(a) : "memory");
    return v;
}
__device__ __forceinline__ float4 lds_f4(uint32_t a) {
    float4 v;
    asm volatile("ld.shared.v4.f32 {%0,%1,%2,%3}, [%4];" : "=f"(v.x), "=f"(v.y), "=f"(v.z), "=f"(v.w) : "r"(a) : "memory");
    return v;
}
__device__ __forceinline__ float lds_bf(uint32_t a) { uint16_t v; asm volatile("ld.shared.b16 %0, [%1];" : "=h"(v) : "r"(a) : "memory"); return __uint_as_float((uint32_t)v << 16); }
__device__ __forceinline__ void bar_arrive(int id, int n) { asm volatile("bar.arrive %0, %1;" ::"r"(id), "r"(n) : "memory"); }
__device__ __forceinline__ void expect_tx(uint32_t bar, uint32_t bytes) {
    asm volatile("mbarrier.arrive.expect_tx.shared::cta.b64 _, [%0], %1;" ::"r"(bar), "r"(bytes) : "memory");
}
__device__ __forceinline__ void bulk_copy(uint32_t dst, const void* src, uint32_t bytes, uint32_t bar) {
    asm volatile("cp.async.bulk.shared::cluster.global.mbarrier::complete_tx::bytes [%0], [%1], %2, [%3];"
                 ::"r"(dst), "l"(src), "r"(bytes), "r"(bar) : "memory");
}
__device__ __forceinline__ void bulk_stream(uint32_t dst, const void* src, uint32_t bytes, uint32_t bar, uint64_t pol) {
    asm volatile("cp.async.bulk.shared::cluster.global.mbarrier::complete_tx::bytes.L2::cache_hint [%0], [%1], %2, [%3], %4;"
                 ::"r"(dst), "l"(src), "r"(bytes), "r"(bar), "l"(pol) : "memory");
}
__device__ __forceinline__ void tensor_stream(uint32_t dst, const CUtensorMap* tm, int c0, int c1, uint32_t bar, uint64_t pol) {
    asm volatile("cp.async.bulk.tensor.2d.shared::cluster.global.mbarrier::complete_tx::bytes.L2::cache_hint [%0], [%1, {%2, %3}], [%4], %5;"
                 ::"r"(dst), "l"(tm), "r"(c0), "r"(c1), "r"(bar), "l"(pol) : "memory");
}
__device__ __forceinline__ uint32_t timer_ns() { uint32_t t; asm volatile("mov.u32 %0, %%globaltimer_lo;" : "=r"(t)); return t; }
__device__ __forceinline__ void pace(uint32_t t0, int dt) {
    while ((int)(timer_ns() - t0) < dt) {}
}
__device__ __forceinline__ uint32_t next_epoch(uint32_t e) { return e + 1 < 3u * 65536u ? e + 1 : 0u; }
__device__ __forceinline__ bool has_tag(uint32_t v, uint32_t tag) { return ((v ^ tag) & 3u) == 0; }
__device__ __forceinline__ void fold_group(const float (*c)[4], float& r0, float& r1) {
    float t[8];
#pragma unroll
    for (int k = 0; k < 4; k++) {
        t[2 * k] = c[k][0] + c[k][3];
        t[2 * k + 1] = c[k][1] + c[k][2];
    }
    const float a0 = t[0] + __shfl_xor_sync(0xffffffffu, t[2], 1), a1 = t[1] + __shfl_xor_sync(0xffffffffu, t[3], 1);
    const float b0 = t[4] + __shfl_xor_sync(0xffffffffu, t[6], 1), b1 = t[5] + __shfl_xor_sync(0xffffffffu, t[7], 1);
    r0 = a0 + __shfl_xor_sync(0xffffffffu, b0, 2);
    r1 = a1 + __shfl_xor_sync(0xffffffffu, b1, 2);
}
constexpr float FIX_SCALE = 268435456.f, FIX_LIMIT = 16384.f;
__device__ __forceinline__ int acc_index(int col) {
    if (ACC_GRP > 8) col = (col & ~63) | ((col & 8) << 2) | ((col & 48) >> 1) | (col & 7);
    return col / ACC_GRP * ACC_PAD + col % ACC_GRP;
}
__device__ __forceinline__ unsigned long long fix_word(float v) {
    return fabsf(v) < FIX_LIMIT ? ((unsigned long long)__float2ll_rn(v * FIX_SCALE) << 14) + 1ull : 129ull;
}
__device__ __forceinline__ unsigned long long atom_add(unsigned long long* p, unsigned long long v) {
    unsigned long long old;
    asm volatile("atom.relaxed.gpu.global.add.u64 %0, [%1], %2;" : "=l"(old) : "l"(p), "l"(v) : "memory");
    return old;
}
__device__ __noinline__ float sum_partials(const float* col, uint32_t tag) {
    float s = 0.f;
    for (int i = 0; i < NS; i++) {
        uint32_t v = ld_rlx(col + i * 8);
        for (int it = 0; !has_tag(v, tag); it++) {
            if (it == SPIN_LIMIT) __trap();
            v = ld_rlx(col + i * 8);
        }
        s += __uint_as_float(v);
    }
    return s;
}

__global__ void __launch_bounds__(NTHREADS, 1)
fused_decode_kernel(const __nv_bfloat16* __restrict__ kc, const __nv_bfloat16* __restrict__ x, Scratch* __restrict__ g,
                    const __nv_bfloat16* __restrict__ wo, __nv_bfloat16* __restrict__ out, const __nv_bfloat16* __restrict__ wq,
                    const __grid_constant__ CUtensorMap tm_wq, const __grid_constant__ CUtensorMap tm_wd,
                    const __grid_constant__ CUtensorMap tm_wg, const __grid_constant__ CUtensorMap tm_wu,
                    const __grid_constant__ CUtensorMap tm_v
                    ) {
    extern __shared__ __align__(1024) unsigned char smem[];
    const int tid = threadIdx.x, warp = tid >> 5, lane = tid & 31;
    constexpr uint32_t sb = 1024;
    if (tid < 192) asm volatile("prefetch.global.L2 [%0];" ::"l"((const char*)kc + ((size_t)(blockIdx.x >> 2) * SK + (blockIdx.x & 3) * 64) * (DH * 2) + tid * 128));
    const uint32_t bar_off = SM_BAR, kempty_off = bar_off + 8 * KSLOTS, vfull_off = kempty_off + 8 * KSLOTS,
                   vempty_off = vfull_off + 8 * VSLOTS, barx_off = vempty_off + 8 * VSLOTS, sfull_off = barx_off + 8,
                   obar_off = sfull_off + 32;

    if (warp == 10) {
        const int cta = blockIdx.x, head = cta >> 2, part = cta & 3;
        const uint32_t kfull = sb + bar_off, kempty = sb + kempty_off, vfull = sb + vfull_off, vempty = sb + vempty_off;
        uint64_t pol = 0;
        const char* kp = (const char*)(kc + ((size_t)head * SK + part * 64) * DH);
        if (lane == 0) {
            TS(12);
#pragma unroll
            for (int i = 0; i < KSLOTS; i++) mbar_init(kfull + 8 * i, 1);
            mbar_init(sb + barx_off, 1);
            asm volatile("fence.mbarrier_init.release.cluster;" ::: "memory");
            asm volatile("fence.proxy.async.shared::cta;" ::: "memory");
            asm volatile("createpolicy.fractional.L2::evict_first.b64 %0, 1.0;" : "=l"(pol));
            TS(16);
            expect_tx(kfull + 8 * POS_K, KSLOT_BYTES);
            bulk_stream(sb + SM_RING + POS_K * KSLOT_BYTES, kp, KSLOT_BYTES, kfull + 8 * POS_K, pol);
            asm volatile("prefetch.tensormap [%0];" ::"l"(&tm_wq) : "memory");
            TS(17);
            expect_tx(sb + barx_off, D * 2 + 16);
            bulk_copy(sb + SM_X, x, D * 2, sb + barx_off);
            bulk_copy(sb + SM_X + D * 2, g->epoch, 16, sb + barx_off);
            TS(19);
        }
        __syncwarp();
        bar_arrive(6, NTHREADS);
        if (lane == 0) {
            expect_tx(kfull, 2 * WQ_BOX);
            tensor_stream(sb + SM_RING, &tm_wq, head * DH, part * P1_ROWS, kfull, pol);
            TS(20);
            tensor_stream(sb + SM_RING + WQ_BOX, &tm_wq, head * DH, part * P1_ROWS + 32, kfull, pol);
#pragma unroll
            for (int i = 1; i < POS_K; i++) {
                expect_tx(kfull + 8 * i, WQ_BOX);
                tensor_stream(sb + SM_RING + i * KSLOT_BYTES, &tm_wq, head * DH, part * P1_ROWS + 32 * (i + 1), kfull + 8 * i, pol);
            }
            asm volatile("prefetch.tensormap [%0];" ::"l"(part < 3 ? &tm_v : &tm_wg) : "memory");
            if (part == 3) {
                asm volatile("prefetch.tensormap [%0];" ::"l"(&tm_wu) : "memory");
                asm volatile("prefetch.tensormap [%0];" ::"l"(&tm_wd) : "memory");
            }
        }
        __syncwarp();
        bar_sync(7, NB7);
        if (lane == 0) {
            TS(1);
            const uint32_t tstart = timer_ns() - TOFF;
            uint64_t poln;
            asm volatile("createpolicy.fractional.L2::evict_normal.b64 %0, 1.0;" : "=l"(poln));
#define WDPOL poln
#pragma unroll 1
            for (int i = POS_K + KFIRST; i < NPOS1; i++) {
                const int s = i & (KSLOTS - 1);
                if (i >= KSLOTS) mbar_wait(kempty + 8 * s, ((i >> 3) - 1) & 1);
                TP(64 + i);
                const int pi = i == 4 ? PI4 : i == 5 ? PI5 : i - (i < PAR(pm, POS_MID) ? PAR(ds, DEPTH_START) : PAR(dm, DEPTH_MID));
                if (pi >= 0) mbar_wait(kfull + 8 * (pi & (KSLOTS - 1)), (pi >> 3) & 1);
                pace(tstart, PAR(ka, KA) + PAR(kb, KB) * (i - POS_K));
                TP(i);
                expect_tx(kfull + 8 * s, KSLOT_BYTES);
                bulk_stream(sb + SM_RING + s * KSLOT_BYTES, kp + (size_t)(i - POS_K) * PARTS * KSLOT_BYTES, KSLOT_BYTES, kfull + 8 * s, pol);
            }
            const int ntile = part < 3 ? NVT : head < NFFN ? 6 : 0, n2 = part < 3 || head >= HEAD_D0 ? ntile + 4 : ntile;
            const char* wp = (const char*)(wo + (size_t)(head * DH + part * CW) * D);
            int s = VSLOT0;
            const int stag = ((cta * 37) & 127) * PAR(td, STAG) / 128;
#pragma unroll 1
            for (int v = 0; v < n2; v++) {
                if (v < VSLOTS) {
                    const int k0 = s * 4 / 3;
                    mbar_wait(kempty + 8 * k0, k0 >> 2);
                    mbar_wait(kempty + 8 * k0 + 8, k0 >> 2);
                } else {
                    mbar_wait(vempty + 8 * s, (v / VSLOTS - 1) & 1);
                }
                TP(64 + NPOS1 + v);
                const int pv = v - (part == 3 ? PAR(df, DEPTH_F) : v < ntile ? PAR(dv, DEPTH_V) : PAR(de, DEPTH_END));
                if (pv >= 0) mbar_wait(vfull + 8 * ((pv + VSLOT0) % VSLOTS), (pv / VSLOTS) & 1);
                else mbar_wait(kfull + 8 * ((NPOS1 + pv) & (KSLOTS - 1)), ((NPOS1 + pv) >> 3) & 1);
                pace(tstart, part < 3 ? PAR(pa, PA) + PAR(pb, PB) * (v < 15 ? v : 15) + PAR(pc, PC) * (v > 15 ? v - 15 : 0) - stag * v / 19
                                      : v < ntile ? PAR(fa, FA) + PAR(fb, FB) * v : PAR(wa, WA) + PAR(wb, WB) * (v - ntile));
                TP(NPOS1 + v);
                const uint32_t full = vfull + 8 * s, dst = sb + SM_RING + s * VSLOT_BYTES;
                if (v >= ntile && part == 3) {
                    const int j = v - ntile;
                    expect_tx(full, DBOX);
                    tensor_stream(dst, &tm_wd, (head - HEAD_D0) * DCOLS, 2 * j * DROWS, full, WDPOL);
                    expect_tx(sb + sfull_off + 8 * j, DBOX);
                    tensor_stream(dst + DBOX, &tm_wd, (head - HEAD_D0) * DCOLS, (2 * j + 1) * DROWS, sb + sfull_off + 8 * j, WDPOL);
                } else if (v >= ntile) {
                    expect_tx(full, BLK16);
                    bulk_stream(dst, wp + (size_t)(v - ntile) * BLK16, BLK16, full, pol);
                } else if (part < 3) {
                    expect_tx(full, VSLOT_BYTES);
                    tensor_stream(dst, &tm_v, part * CW, head * SK + v * 256, full, pol);
                    if (v == PAR(tp, GPOS)) {
                        expect_tx(sb + barx_off, D * 4);
                        bulk_copy(sb + SM_S, g->xg, D * 4, sb + barx_off);
                    }
                    const int st = v == 0 ? 0 : (v + SLEAD) >> 2;
                    if (v == 0 || (((v + SLEAD) & 3) == 0 && st < 4)) {
                        expect_tx(sb + sfull_off + 8 * st, 4096);
                        bulk_copy(sb + SM_S + st * 4096, g->xs + head * SK + st * 1024, 4096, sb + sfull_off + 8 * st);
                    }
                } else {
                    const int t = v < 3 ? v : v - 3;
                    const CUtensorMap* tm = v < 3 ? &tm_wg : &tm_wu;
                    expect_tx(full, t < 2 ? VSLOT_BYTES : VSLOT_BYTES / 2);
                    tensor_stream(dst, tm, head * CW, t * 256, full, pol);
                    if (t < 2) tensor_stream(dst + VSLOT_BYTES / 2, tm, head * CW, t * 256 + 128, full, pol);
                }
                s = s == VSLOTS - 1 ? 0 : s + 1;
            }
            TS(2);
            TSDUMP(0x1b1006);
        }
        return;
    }

    const int cta = __shfl_sync(0xffffffffu, (int)blockIdx.x, 0), head = cta >> 2, part = cta & 3;
    const uint32_t kfull = sb + bar_off, kempty = sb + kempty_off, vfull = sb + vfull_off, vempty = sb + vempty_off;

    const int n = lane >> 2, t4 = lane & 3, n0 = t4 * 2, r8 = lane & 7;
    const bool is_hi = n == n0 + 1, diag = n == n0 || is_hi;
    const int dsh = is_hi ? 16 : 0;
    uint32_t offv[4];
#pragma unroll
    for (int i = 0; i < 4; i++) offv[i] = (uint32_t)(((2 * i + ((lane >> 3) & 1)) ^ r8) * 16);
    const int keyv = r8 + 8 * (lane >> 4);
    const uint32_t red = sb + SM_RED + warp * RED_STRIDE;

    if (warp == 9) {
        if (lane == 0) {
#pragma unroll
            for (int i = 0; i < KSLOTS; i++) mbar_init(kempty + 8 * i, 8);
#pragma unroll
            for (int i = 0; i < VSLOTS; i++) {
                mbar_init(vfull + 8 * i, 1);
                mbar_init(vempty + 8 * i, 8);
            }
#pragma unroll
            for (int i = 0; i < 4; i++) mbar_init(sb + sfull_off + 8 * i, 1);
            mbar_init(sb + obar_off, 2);
            asm volatile("fence.mbarrier_init.release.cluster;" ::: "memory");
            asm volatile("fence.proxy.async.shared::cta;" ::: "memory");
        }
        __syncwarp();
        bar_arrive(7, NB7);
    }
    float* const xq = g->xq + head * PARTS * DH + tid;
    uint32_t pv[PARTS] = {0, 0, 0, 0};
    if (warp < 6) st_rlx(xq + part * DH, 0u);
    bar_sync(6, NTHREADS);
    mbar_wait(sb + barx_off, 0);
    if (tid == 0) TS(21);
    const uint32_t epoch = next_epoch(lds_u(sb + SM_X + D * 2));
    const uint32_t tag = epoch % 3u + 1u, tag16 = epoch & 0xffffu;

    float ln_m, ln_d;
    {
        float v[20];
#pragma unroll
        for (int i = 0; i < 10; i++) {
            const uint32_t u = lds_u(sb + SM_X + (lane + 32 * i) * 4);
            v[2 * i] = __uint_as_float(u << 16);
            v[2 * i + 1] = __uint_as_float(u & 0xffff0000u);
        }
        float sum = 0.f, sq = 0.f;
#pragma unroll
        for (int i = 0; i < 20; i++) sum += v[i];
#pragma unroll
        for (int o = 16; o; o >>= 1) sum += __shfl_xor_sync(0xffffffffu, sum, o);
        const float mean = sum * (1.0f / D);
#pragma unroll
        for (int i = 0; i < 20; i++) sq = fmaf(v[i] - mean, v[i] - mean, sq);
#pragma unroll
        for (int o = 16; o; o >>= 1) sq += __shfl_xor_sync(0xffffffffu, sq, o);
        ln_m = bf16r(mean);
        ln_d = bf16r(__fsqrt_rn(bf16r(bf16r(sq * (1.0f / D)) + 1e-5f)));
    }
    auto xn = [&](float xv) -> float { return __fdividef(bf16r(xv - ln_m), ln_d); };
    if (tid == 0) TS(18);

    {
        const uint32_t xr = sb + SM_X + (part * P1_ROWS + warp * 16 + n) * 2;
        const uint32_t b0 = diag ? bf16bits(xn(lds_bf(xr))) << dsh : 0u, b1 = diag ? bf16bits(xn(lds_bf(xr + 16))) << dsh : 0u;
        const int s = warp < 4 ? 0 : (warp >> 1) - 1;
        mbar_wait(kfull + 8 * s, 0);
        const uint32_t base = sb + SM_RING + s * KSLOT_BYTES + ((warp < 4 ? warp : warp & 1) * 16 + keyv) * (DH * 2);
        float c[12][4];
#pragma unroll
        for (int i = 0; i < 12; i++) {
            uint32_t a[4];
            c[i][0] = c[i][1] = c[i][2] = c[i][3] = 0.f;
            ldsm4t(a, base + (i >> 2) * 128 + offv[i & 3]);
            mma16816(c[i], a, b0, b1);
        }
        __syncwarp();
        if (lane < (warp < 4 ? 2 : 4)) mbar_arrive(kempty + 8 * s);
#pragma unroll
        for (int g = 0; g < 3; g++) {
            float r0, r1;
            fold_group(c + 4 * g, r0, r1);
            sts_f(red + ((g * 8 + n0) * 8 + n) * 4, r0);
            sts_f(red + ((g * 8 + n0 + 1) * 8 + n) * 4, r1);
        }
    }

    const bool gemv = part < 3 || head < NFFN;
    const int n4 = part < 3 ? 320 : 256;
    if (warp < 8) {
        if (warp < 6) {
            bar_sync(1, 320);
            if (tid == 0) TS(5);
            float s = 0.f;
#pragma unroll
            for (int w = 0; w < 10; w++) s += lds_f(sb + SM_RED + w * RED_STRIDE + tid * 4);
            const uint32_t own = tagged(s, tag);
            st_rlx(xq + part * DH, own);
            const uint32_t tg = next_epoch(lds_u(sb + SM_X + D * 2)) % 3u + 1u;
#pragma unroll
            for (int j = 0; j < PARTS; j++) pv[j] = 0;
#pragma unroll
            for (int j = 0; j < PARTS; j++)
                if (j == part) pv[j] = own;
#pragma unroll 1
            for (int it = 0;; it++) {
                if (has_tag(pv[0], tg) && has_tag(pv[1], tg) && has_tag(pv[2], tg) && has_tag(pv[3], tg)) break;
                if (it == SPIN_LIMIT) __trap();
                if (it) __nanosleep(SLEEP_Q);
#pragma unroll
                for (int j = 0; j < PARTS; j++)
                    if (!has_tag(pv[j], tg)) pv[j] = ld_rlx(xq + j * DH);
            }
            const float q = (__uint_as_float(pv[0]) + __uint_as_float(pv[1])) + (__uint_as_float(pv[2]) + __uint_as_float(pv[3]));
            asm volatile("st.shared.b16 [%0], %1;" ::"r"(sb + SM_Q + tid * 2), "h"((uint16_t)bf16bits(q)) : "memory");
        } else {
            bar_arrive(1, 320);
        }
        bar_sync(2, 256);
        if (tid == 0) TS(6);

        {
            const int grp = warp >> 2;
            uint32_t qb[12][2], offk[4];
#pragma unroll
            for (int i = 0; i < 12; i++)
#pragma unroll
                for (int e = 0; e < 2; e++) qb[i][e] = lds_u(sb + SM_Q + (((i >> 2) * 8 + ((2 * (i & 3) + e) ^ n)) * 8 + n0) * 2);
#pragma unroll
            for (int i = 0; i < 4; i++) offk[i] = (uint32_t)(((2 * i + (lane >> 4)) ^ r8) * 16);
            const uint32_t rowk = sb + SM_RING + ((warp & 3) * 16 + r8 + 8 * ((lane >> 3) & 1)) * (DH * 2);
            uint32_t* xs_out = g->xs + head * SK + (grp * PARTS + part) * 64 + (warp & 3) * 16 + n;
#pragma unroll 1
            for (int u = 0; u < NKT / 2; u++) {
                const int i = POS_K + 2 * u + grp, s = i & (KSLOTS - 1);
                mbar_wait(kfull + 8 * s, (i >> 3) & 1);
                const uint32_t base = rowk + s * KSLOT_BYTES;
                float c[3][4];
#pragma unroll
                for (int g = 0; g < 3; g++) c[g][0] = c[g][1] = c[g][2] = c[g][3] = 0.f;
#pragma unroll
                for (int k = 0; k < 4; k++)
#pragma unroll
                    for (int g = 0; g < 3; g++) {
                        uint32_t a[4];
                        ldsm4(a, base + g * 128 + offk[k]);
                        mma16816(c[g], a, qb[g * 4 + k][0], qb[g * 4 + k][1]);
                    }
                __syncwarp();
                if (lane < 2) mbar_arrive(kempty + 8 * s);
                const float d0 = is_hi ? c[0][1] + c[1][1] + c[2][1] : c[0][0] + c[1][0] + c[2][0];
                const float d1 = is_hi ? c[0][3] + c[1][3] + c[2][3] : c[0][2] + c[1][2] + c[2][2];
                if (diag) {
                    st_rlx(xs_out, (bf16bits(bf16r(d0) * 0.07216878364870322f) << 16) | tag16);
                    st_rlx(xs_out + 8, (bf16bits(bf16r(d1) * 0.07216878364870322f) << 16) | tag16);
                }
                xs_out += 2 * PARTS * 64;
            }
        }
        if (tid == 0) TS(7);

        const uint32_t rowv = sb + SM_RING + keyv * 128;
        int s = VSLOT0, ph = 0;
        if (part < 3) {
            float acc[4][4], m = -INFINITY, l = 0.f, scale = 0.f;
#pragma unroll
            for (int k = 0; k < 4; k++) acc[k][0] = acc[k][1] = acc[k][2] = acc[k][3] = 0.f;
            const uint32_t pw = sb + SM_P + warp * 256;
            const uint32_t pst = pw + ((lane >> 3) * 16 + (lane & 1) * 8 + ((lane >> 2) & 1) * 2 + ((lane >> 1) & 1)) * 4;
#pragma unroll 1
            for (int st = 0; st < 4; st++) {
                const int key0 = st * 1024 + (lane >> 3) * 256 + warp * 32 + r8 * 4;
                mbar_wait(sb + sfull_off + 8 * st, 0);
                uint4 sc = lds_u4(sb + SM_S + key0 * 4);
#pragma unroll 1
                for (int it = 0;; it++) {
                    if (((((sc.x ^ tag16) | (sc.y ^ tag16)) | ((sc.z ^ tag16) | (sc.w ^ tag16))) & 0xffffu) == 0) break;
                    if (it == SPIN_LIMIT) __trap();
                    if (it) __nanosleep(100);
                    sc = ld_rlx4(g->xs + head * SK + key0);
                }
                const float s0 = __uint_as_float(sc.x & 0xffff0000u), s1 = __uint_as_float(sc.y & 0xffff0000u);
                const float s2 = __uint_as_float(sc.z & 0xffff0000u), s3 = __uint_as_float(sc.w & 0xffff0000u);
                __syncwarp();
                float mn = fmaxf(fmaxf(s0, s1), fmaxf(s2, s3));
#pragma unroll
                for (int o = 16; o; o >>= 1) mn = fmaxf(mn, __shfl_xor_sync(0xffffffffu, mn, o));
                mn = fmaxf(mn, m);
                const float f = exp2f((m - mn) * 1.4426950408889634f);
                m = mn;
                const float p0 = exp2f((s0 - m) * 1.4426950408889634f), p1 = exp2f((s1 - m) * 1.4426950408889634f);
                const float p2 = exp2f((s2 - m) * 1.4426950408889634f), p3 = exp2f((s3 - m) * 1.4426950408889634f);
                l = l * f + ((p0 + p1) + (p2 + p3));
#pragma unroll
                for (int k = 0; k < 4; k++) { acc[k][0] *= f; acc[k][2] *= f; }
                sts_u(pst, pack2(p0, p1));
                sts_u(pst + 16, pack2(p2, p3));
                __syncwarp();
                if (st == 0 && tid == 0) TS(11);
                if (st == 3) {
#pragma unroll
                    for (int o = 16; o; o >>= 1) l += __shfl_xor_sync(0xffffffffu, l, o);
                    if (lane == 0) { sts_f(sb + SM_MISC + warp * 4, m); sts_f(sb + SM_MISC + 32 + warp * 4, l); }
                    bar_sync(3, 256);
                    const float mw = lds_f(sb + SM_MISC + r8 * 4), lw = lds_f(sb + SM_MISC + 32 + r8 * 4);
                    float mm = mw;
#pragma unroll
                    for (int o = 4; o; o >>= 1) mm = fmaxf(mm, __shfl_xor_sync(0xffffffffu, mm, o));
                    float ls = lw * exp2f((mw - mm) * 1.4426950408889634f);
#pragma unroll
                    for (int o = 4; o; o >>= 1) ls += __shfl_xor_sync(0xffffffffu, ls, o);
                    scale = __fdividef(exp2f((m - mm) * 1.4426950408889634f), ls);
                    if (tid == 0) TS(10);
                }
#pragma unroll 1
                for (int u = 0; u < 4; u++) {
                    const uint4 pb = lds_u4(pw + u * 64 + t4 * 16);
                    mbar_wait(vfull + 8 * s, ph);
                    const uint32_t base = rowv + s * VSLOT_BYTES + warp * 32 * 128;
                    uint32_t a[8][4];
#pragma unroll
                    for (int k = 0; k < 8; k++) ldsm4t(a[k], base + (k >> 2) * 2048 + offv[k & 3]);
#pragma unroll
                    for (int k = 0; k < 8; k++) mma16816(acc[k & 3], a[k], k < 4 ? pb.x : pb.z, k < 4 ? pb.y : pb.w);
                    __syncwarp();
                    if (lane == 0) mbar_arrive(vempty + 8 * s);
                    if (++s == VSLOTS) s = 0;
                    if (s == VSLOT0) ph ^= 1;
                }
            }
            if (tid == 0) TS(8);
            const float o0 = t4 == 0 ? acc[0][0] : t4 == 1 ? acc[1][0] : t4 == 2 ? acc[2][0] : acc[3][0];
            const float o1 = t4 == 0 ? acc[0][2] : t4 == 1 ? acc[1][2] : t4 == 2 ? acc[2][2] : acc[3][2];
            sts_f(sb + SM_RED + ((t4 * 16 + n) * 8 + (warp ^ t4)) * 4, o0 * scale);
            sts_f(sb + SM_RED + ((t4 * 16 + 8 + n) * 8 + (warp ^ t4)) * 4, o1 * scale);
        } else if (gemv) {
#pragma unroll 1
            for (int mat = 0; mat < 2; mat++) {
                float acc[4][4];
#pragma unroll
                for (int k = 0; k < 4; k++) acc[k][0] = acc[k][1] = acc[k][2] = acc[k][3] = 0.f;
#pragma unroll 1
                for (int t = 0; t < 3; t++) {
                    mbar_wait(vfull + 8 * s, 0);
#pragma unroll 1
                    for (int ks = 0; ks < (t < 2 ? 2 : 1); ks++) {
                        const int row = t < 2 ? warp * 32 + ks * 16 : warp * 16;
                        const uint32_t u0 = lds_u(sb + SM_X + (t * 256 + row + n0) * 2), u1 = lds_u(sb + SM_X + (t * 256 + row + 8 + n0) * 2);
                        const uint32_t b0 = pack2(xn(__uint_as_float(u0 << 16)), xn(__uint_as_float(u0 & 0xffff0000u)));
                        const uint32_t b1 = pack2(xn(__uint_as_float(u1 << 16)), xn(__uint_as_float(u1 & 0xffff0000u)));
#pragma unroll
                        for (int k = 0; k < 4; k++) {
                            uint32_t a[4];
                            ldsm4t(a, rowv + s * VSLOT_BYTES + row * 128 + offv[k]);
                            mma16816(acc[k], a, b0, b1);
                        }
                    }
                    __syncwarp();
                    if (lane == 0) mbar_arrive(vempty + 8 * s);
                    if (++s == VSLOTS) s = 0;
                }
                const float o0 = t4 == 0 ? acc[0][0] : t4 == 1 ? acc[1][0] : t4 == 2 ? acc[2][0] : acc[3][0];
                const float o1 = t4 == 0 ? acc[0][2] : t4 == 1 ? acc[1][2] : t4 == 2 ? acc[2][2] : acc[3][2];
                sts_f(sb + SM_RED + mat * 2048 + ((t4 * 16 + n) * 8 + (warp ^ t4)) * 4, o0);
                sts_f(sb + SM_RED + mat * 2048 + ((t4 * 16 + 8 + n) * 8 + (warp ^ t4)) * 4, o1);
            }
        }
        if (gemv) {
            if (warp < 2) {
                bar_sync(4, n4);
                const float4 a0 = lds_f4(sb + SM_RED + tid * 32), a1 = lds_f4(sb + SM_RED + tid * 32 + 16);
                float r = ((a0.x + a0.y) + (a0.z + a0.w)) + ((a1.x + a1.y) + (a1.z + a1.w));
                if (part == 3) {
                    const float4 u0 = lds_f4(sb + SM_RED + 2048 + tid * 32), u1 = lds_f4(sb + SM_RED + 2048 + tid * 32 + 16);
                    r = bf16r(silu(bf16r(r))) * bf16r(((u0.x + u0.y) + (u0.z + u0.w)) + ((u1.x + u1.y) + (u1.z + u1.w)));
                    st_rlx(g->xh + head * CW + tid, (bf16bits(r) << 16) | tag16);
                } else {
                    sts_u(sb + SM_O + tid * 4, bf16bits(r));
                    __syncwarp();
                    if (lane == 0) mbar_arrive(sb + obar_off);
                }
            } else {
                bar_arrive(4, n4);
            }
        }
    } else {
        bar_arrive(1, 320);
        if (smem_addr(smem) != sb) __trap();
        if (part < 3) bar_sync(4, 320);
    }

    if (part < 3) {
        float* const dst = g->ps + ((size_t)(warp * 8 + n0) * NS + head * 3 + part) * 8 + n;
        const uint32_t roww = sb + SM_RING + keyv * ROW_BYTES + warp * 128;
        const int col = (warp * 8 + n0) * 8 + n;
        mbar_wait(sb + barx_off, 1);
        uint32_t g0 = lds_u(sb + SM_S + col * 4), g1 = lds_u(sb + SM_S + col * 4 + 32);
#pragma unroll 1
        for (int it = 0; (((g0 ^ tag16) | (g1 ^ tag16)) & 0xffffu) != 0; it++) {
            if (it == SPIN_LIMIT) __trap();
            g0 = ld_rlx(g->xg + col);
            g1 = ld_rlx(g->xg + col + 8);
        }
        __syncwarp();
        const float x0 = lds_bf(sb + SM_X + col * 2), x1 = lds_bf(sb + SM_X + col * 2 + 16);
        unsigned long long* const acc = g->acc + acc_index(col);
        uint32_t a[4][4][4];
        auto load_block = [&](int ks) {
            const int s = (NVT + ks + VSLOT0) % VSLOTS;
            mbar_wait(vfull + 8 * s, ((NVT + ks) / VSLOTS) & 1);
#pragma unroll
            for (int k = 0; k < 4; k++) ldsm4t(a[ks][k], roww + s * VSLOT_BYTES + offv[k]);
        };
#pragma unroll
        for (int ks = 0; ks < NPRE; ks++) load_block(ks);
        mbar_wait(sb + obar_off, 0);
        if (tid == 0) TS(9);
        uint32_t bo[4][2];
#pragma unroll
        for (int i = 0; i < 8; i++) {
            const uint32_t u = lds_u(sb + SM_O + (i * 8 + n) * 4);
            bo[i >> 1][i & 1] = diag ? u << dsh : 0u;
        }
        float c[4][4];
#pragma unroll
        for (int k = 0; k < 4; k++) c[k][0] = c[k][1] = c[k][2] = c[k][3] = 0.f;
#pragma unroll
        for (int ks = 0; ks < 4; ks++) {
            if (ks >= NPRE) load_block(ks);
#pragma unroll
            for (int k = 0; k < 4; k++) mma16816(c[k], a[ks][k], bo[ks][0], bo[ks][1]);
        }
        if (tid == 0) TS(14);
        float r0, r1;
        fold_group(c, r0, r1);
        const unsigned long long w0 = fix_word(r0), w1 = fix_word(r1);
        const unsigned long long t0 = atom_add(acc, w0) + w0, t1 = atom_add(acc + (ACC_GRP > 8 ? 32 : 8) / ACC_GRP * ACC_PAD, w1) + w1;
        st_rlx(dst, tagged(r0, tag));
        st_rlx(dst + NS * 8, tagged(r1, tag));
        if (tid == 0) TS(15);
        auto finish = [&](unsigned long long t, int e, uint32_t gate, float xv) {
            if ((t & 127u) != NS) return;
            float sv = __ll2float_rn((long long)t >> 14) * (1.0f / FIX_SCALE);
            if (t & (127u << 7)) sv = sum_partials(g->ps + (size_t)(warp * 8 + n0 + e) * NS * 8 + n, tag);
            out[col + 8 * e] = __float2bfloat16_rn(xv + bf16r(bf16r(sv) * __uint_as_float(gate & 0xffff0000u)));
            if (col + e == 0) st_rlx(g->epoch, epoch);
        };
        finish(t0, 0, g0, x0);
        finish(t1, 1, g1, x1);
        if (tid == 0) TS(4);
    }

    if (part == 3 && head >= HEAD_D0) {
        if (warp < 6) {
            const uint32_t* src = g->xh + tid * 8;
            uint4 h0, h1;
#pragma unroll 1
            for (int it = 0;; it++) {
                h0 = ld_rlx4(src);
                h1 = ld_rlx4(src + 4);
                const uint32_t bad = ((h0.x ^ tag16) | (h0.y ^ tag16)) | ((h0.z ^ tag16) | (h0.w ^ tag16)) |
                                     ((h1.x ^ tag16) | (h1.y ^ tag16)) | ((h1.z ^ tag16) | (h1.w ^ tag16));
                if ((bad & 0xffffu) == 0) break;
                if (it == SPIN_LIMIT) __trap();
                __nanosleep(500);
            }
            const uint32_t hs = sb + SM_S + (tid >> 2) * 64 + (tid & 3) * 4;
            sts_u(hs, __byte_perm(h0.x, h0.y, 0x7632));
            sts_u(hs + 16, __byte_perm(h0.z, h0.w, 0x7632));
            sts_u(hs + 32, __byte_perm(h1.x, h1.y, 0x7632));
            sts_u(hs + 48, __byte_perm(h1.z, h1.w, 0x7632));
            bar_sync(3, 192);
            if (tid == 0) TS(9);
            uint4 hb[8];
#pragma unroll
            for (int b = 0; b < 8; b++) hb[b] = lds_u4(sb + SM_S + (b * 6 + warp) * 64 + t4 * 16);
            const int v0 = head < NFFN ? 6 : 0;
            const uint32_t rowd = sb + SM_RING + (warp * 32 + keyv) * 64;
            const uint32_t c0 = (((lane >> 3) & 1) ^ (r8 >> 1)) * 16, c1 = c0 ^ 32;
            float c[4][4];
#pragma unroll
            for (int k = 0; k < 4; k++) c[k][0] = c[k][1] = c[k][2] = c[k][3] = 0.f;
            uint32_t a[2][4][4];
#pragma unroll
            for (int b = 0; b <= 8; b++) {
                if (b < 8) {
                    const int s = (VSLOT0 + (b >> 1)) % VSLOTS;
                    if (b & 1) mbar_wait(sb + sfull_off + 8 * (b >> 1), 0);
                    else mbar_wait(vfull + 8 * s, v0 / VSLOTS);
                    const uint32_t base = rowd + s * VSLOT_BYTES + (b & 1) * DBOX;
                    ldsm4t(a[b & 1][0], base + c0);
                    ldsm4t(a[b & 1][1], base + c1);
                    ldsm4t(a[b & 1][2], base + 1024 + c0);
                    ldsm4t(a[b & 1][3], base + 1024 + c1);
                }
                if (b > 0) {
                    const uint4 hv = hb[b - 1];
                    mma16816(c[0], a[~b & 1][0], hv.x, hv.y);
                    mma16816(c[1], a[~b & 1][1], hv.x, hv.y);
                    mma16816(c[2], a[~b & 1][2], hv.z, hv.w);
                    mma16816(c[3], a[~b & 1][3], hv.z, hv.w);
                }
            }
            const float f = t4 == 0 ? c[0][0] + c[2][0] : t4 == 1 ? c[0][2] + c[2][2] : t4 == 2 ? c[1][0] + c[3][0] : c[1][2] + c[3][2];
            sts_f(sb + SM_P + warp * 128 + (t4 * 8 + n) * 4, f);
            bar_arrive(5, 224);
        } else if (warp == 8) {
            const int col = (head - HEAD_D0) * DCOLS + lane;
            asm volatile("st.relaxed.gpu.global.u64 [%0], %1;" ::"l"(g->acc + acc_index(col)), "l"(0ull) : "memory");
            __threadfence();
            bar_sync(5, 224);
            float t = 0.f;
#pragma unroll
            for (int w = 0; w < 6; w++) t += lds_f(sb + SM_P + w * 128 + lane * 4);
            st_rlx(g->xg + col, (bf16bits(silu(bf16r(t))) << 16) | tag16);
        }
    }
}

typedef CUresult (*EncodeFn)(CUtensorMap*, CUtensorMapDataType, cuuint32_t, void*, const cuuint64_t*, const cuuint64_t*,
                             const cuuint32_t*, const cuuint32_t*, CUtensorMapInterleave, CUtensorMapSwizzle,
                             CUtensorMapL2promotion, CUtensorMapFloatOOBfill);

#define WD_PROMO CU_TENSOR_MAP_L2_PROMOTION_L2_128B
#define PROMO CU_TENSOR_MAP_L2_PROMOTION_L2_128B
void encode_2d(EncodeFn fn, CUtensorMap* tm, void* base, int cols, int rows, int box_cols, int box_rows, CUtensorMapSwizzle swz,
               CUtensorMapL2promotion promo = PROMO) {
    const cuuint64_t dims[2] = {(cuuint64_t)cols, (cuuint64_t)rows};
    const cuuint64_t strides[1] = {(cuuint64_t)cols * 2};
    const cuuint32_t box[2] = {(cuuint32_t)box_cols, (cuuint32_t)box_rows};
    const cuuint32_t estr[2] = {1, 1};
    fn(tm, CU_TENSOR_MAP_DATA_TYPE_BFLOAT16, 2, base, dims, strides, box, estr, CU_TENSOR_MAP_INTERLEAVE_NONE, swz, promo,
       CU_TENSOR_MAP_FLOAT_OOB_FILL_NONE);
}

}

extern "C" void kernel_launch(void* const* d_in, const int* in_sizes, int n_in, void* d_out, int out_size) {
    static EncodeFn encode = nullptr;
    static Scratch* scratch = nullptr;
    if (!encode) {
        cudaDriverEntryPointQueryResult qr;
        cudaGetDriverEntryPoint("cuTensorMapEncodeTiled", (void**)&encode, cudaEnableDefault, &qr);
        cudaGetSymbolAddress((void**)&scratch, g_scratch);
        cudaFuncSetAttribute(fused_decode_kernel, cudaFuncAttributeMaxDynamicSharedMemorySize, SMEM_BYTES);
    }
    CUtensorMap tm_wq, tm_wd, tm_wg, tm_wu, tm_v;
    encode_2d(encode, &tm_wq, d_in[3], H * DH, D, DH, 32, CU_TENSOR_MAP_SWIZZLE_NONE);
    encode_2d(encode, &tm_wd, d_in[8], D, F, DCOLS, DROWS, CU_TENSOR_MAP_SWIZZLE_64B, WD_PROMO);
    encode_2d(encode, &tm_wg, d_in[6], F, D, CW, 128, CU_TENSOR_MAP_SWIZZLE_128B);
    encode_2d(encode, &tm_wu, d_in[7], F, D, CW, 128, CU_TENSOR_MAP_SWIZZLE_128B);
    encode_2d(encode, &tm_v, d_in[2], DH, H * SK, CW, 256, CU_TENSOR_MAP_SWIZZLE_128B);
    fused_decode_kernel<<<NCTA, NTHREADS, SMEM_BYTES, cudaStreamPerThread>>>(
        (const __nv_bfloat16*)d_in[1], (const __nv_bfloat16*)d_in[0], scratch, (const __nv_bfloat16*)d_in[4],
        (__nv_bfloat16*)d_out, (const __nv_bfloat16*)d_in[3], tm_wq, tm_wd, tm_wg, tm_wu, tm_v
        );
}
```

```cpp
#include <cuda.h>
#include <cuda_runtime.h>
#include <cuda_bf16.h>
#include <stdint.h>

namespace {

constexpr int D = 640, H = 32, DH = 192, SK = 4096, F = 1536;
constexpr int PARTS = 4, NCTA = H * PARTS, NTHREADS = 352;
constexpr int KSLOTS = 8, KSLOT_BYTES = 24576;
constexpr int VSLOTS = 6, VSLOT_BYTES = 32768;
constexpr int NKT = 16, NVT = 16;
constexpr int POS_K = 4, NPOS1 = POS_K + NKT;
constexpr int VSLOT0 = 3;
constexpr int CW = 64;
constexpr int WO_BLK = 16 * D * 2;
constexpr int NFFN = F / CW;
constexpr int NS = H * 3;
constexpr int P1_ROWS = D / PARTS;
constexpr int WQ_BOX = 32 * DH * 2;
constexpr int DCOLS = 32, DROWS = 192;
constexpr int DBOX = DCOLS * DROWS * 2;
constexpr int HEAD_D0 = H - D / DCOLS;
constexpr int SPIN_LIMIT = 1 << 20;
constexpr uint32_t WAIT_CLOCKS = 1u << 30;
constexpr float LOG2E = 1.4426950408889634f, SCORE_SCALE = 0.07216878364870322f;

constexpr int T_START = 650;
constexpr int T_K0 = 1000, T_K = 980, T_V0 = 17300, T_V = 1095, T_WO = 560, T_WD0 = 23500, T_WD = 1400;
constexpr int DEPTH = 4, DEPTH_F = 6;
constexpr int GATE_POS = 15;

constexpr uint32_t SB = 1024;
constexpr uint32_t SM_RING = SB;
constexpr uint32_t SM_S = SM_RING + KSLOTS * KSLOT_BYTES;
constexpr uint32_t SM_X = SM_S + SK * 4;
constexpr uint32_t SM_RED = SM_X + 1408;
constexpr uint32_t RED_STRIDE = DH * 4;
constexpr uint32_t SM_P = SM_RED + 10 * RED_STRIDE;
constexpr uint32_t SM_Q = SM_P + 8 * 256;
constexpr uint32_t SM_O = SM_Q + DH * 2;
constexpr uint32_t SM_MISC = SM_O + CW * 4;
constexpr uint32_t KFULL = SM_MISC + 64, KEMPTY = KFULL + 8 * KSLOTS, VFULL = KEMPTY + 8 * KSLOTS,
                   VEMPTY = VFULL + 8 * VSLOTS, XBAR = VEMPTY + 8 * VSLOTS, SFULL = XBAR + 8, OBAR = SFULL + 32;
constexpr int SMEM_BYTES = KFULL + 320 - SB;

constexpr size_t SCRATCH_ALIGN = 1 << 18;
constexpr int ACC_OFF = 32, ACC_PAIR = 96, ACC_STEP = 512;
struct __align__(128) Scratch {
    unsigned long long acc[D / 32 * ACC_STEP + 512];
    unsigned epoch[128];
    float xq[NCTA * DH];
    uint32_t xs[H * SK];
    uint32_t xh[F];
    uint32_t xg[D];
    float big[D];
};
__device__ __align__(128) unsigned char g_scratch[sizeof(Scratch) + SCRATCH_ALIGN];

__device__ __forceinline__ void mbar_init(uint32_t bar, uint32_t cnt) {
    asm volatile("mbarrier.init.shared::cta.b64 [%0], %1;" ::"r"(bar), "r"(cnt) : "memory");
}
__device__ __forceinline__ void mbar_init_fence() {
    asm volatile("fence.mbarrier_init.release.cluster;" ::: "memory");
    asm volatile("fence.proxy.async.shared::cta;" ::: "memory");
}
__device__ __forceinline__ void mbar_arrive(uint32_t bar) {
    asm volatile("mbarrier.arrive.shared::cta.b64 _, [%0];" ::"r"(bar) : "memory");
}
__device__ __forceinline__ bool mbar_try(uint32_t bar, uint32_t parity) {
    uint32_t ok;
    asm volatile("{\n.reg .pred p;\nmbarrier.try_wait.parity.shared::cta.b64 p, [%1], %2;\nselp.u32 %0, 1, 0, p;\n}"
                 : "=r"(ok) : "r"(bar), "r"(parity) : "memory");
    return ok;
}
__device__ __forceinline__ bool mbar_test(uint32_t bar, uint32_t parity) {
    uint32_t ok;
    asm volatile("{\n.reg .pred p;\nmbarrier.test_wait.parity.shared::cta.b64 p, [%1], %2;\nselp.u32 %0, 1, 0, p;\n}"
                 : "=r"(ok) : "r"(bar), "r"(parity) : "memory");
    return ok;
}
__device__ __forceinline__ void mbar_wait(uint32_t bar, uint32_t parity) {
    if (mbar_try(bar, parity)) return;
    const uint32_t t0 = (uint32_t)clock();
#pragma unroll 1
    while (!mbar_try(bar, parity))
        if ((uint32_t)clock() - t0 > WAIT_CLOCKS) __trap();
}
__device__ __forceinline__ void mbar_spin(uint32_t bar, uint32_t parity) {
#pragma unroll 1
    for (uint32_t it = 0; !mbar_test(bar, parity); it++)
        if (it > (1u << 26)) __trap();
}
__device__ __forceinline__ void bar_sync(int id, int n) { asm volatile("bar.sync %0, %1;" ::"r"(id), "r"(n) : "memory"); }
__device__ __forceinline__ void bar_arrive(int id, int n) { asm volatile("bar.arrive %0, %1;" ::"r"(id), "r"(n) : "memory"); }
__device__ __forceinline__ void ldsm4(uint32_t (&a)[4], uint32_t addr) {
    asm volatile("ldmatrix.sync.aligned.m8n8.x4.shared.b16 {%0,%1,%2,%3}, [%4];"
                 : "=r"(a[0]), "=r"(a[1]), "=r"(a[2]), "=r"(a[3]) : "r"(addr) : "memory");
}
__device__ __forceinline__ void ldsm4t(uint32_t (&a)[4], uint32_t addr) {
    asm volatile("ldmatrix.sync.aligned.m8n8.x4.trans.shared.b16 {%0,%1,%2,%3}, [%4];"
                 : "=r"(a[0]), "=r"(a[1]), "=r"(a[2]), "=r"(a[3]) : "r"(addr) : "memory");
}
__device__ __forceinline__ void mma16816(float (&c)[4], const uint32_t (&a)[4], uint32_t b0, uint32_t b1) {
    asm volatile("mma.sync.aligned.m16n8k16.row.col.f32.bf16.bf16.f32 {%0,%1,%2,%3}, {%4,%5,%6,%7}, {%8,%9}, {%0,%1,%2,%3};"
                 : "+f"(c[0]), "+f"(c[1]), "+f"(c[2]), "+f"(c[3])
                 : "r"(a[0]), "r"(a[1]), "r"(a[2]), "r"(a[3]), "r"(b0), "r"(b1));
}
__device__ __forceinline__ float bf16r(float v) { return __bfloat162float(__float2bfloat16_rn(v)); }
__device__ __forceinline__ uint32_t bf16bits(float v) { return (uint32_t)__bfloat16_as_ushort(__float2bfloat16_rn(v)); }
__device__ __forceinline__ uint32_t pack2(float lo, float hi) {
    uint32_t r;
    asm("cvt.rn.bf16x2.f32 %0, %1, %2;" : "=r"(r) : "f"(hi), "f"(lo));
    return r;
}
__device__ __forceinline__ float silu(float v) { return __fdividef(v, 1.0f + __expf(-v)); }
__device__ __forceinline__ void st_rlx(void* p, uint32_t v) {
    asm volatile("st.relaxed.gpu.global.b32 [%0], %1;" ::"l"(p), "r"(v) : "memory");
}
__device__ __forceinline__ uint32_t ld_rlx(const void* p) {
    uint32_t v;
    asm volatile("ld.relaxed.gpu.global.b32 %0, [%1];" : "=r"(v) : "l"(p) : "memory");
    return v;
}
__device__ __forceinline__ uint4 ld_rlx4(const void* p) {
    uint4 v;
    asm volatile("ld.relaxed.gpu.global.v4.b32 {%0,%1,%2,%3}, [%4];" : "=r"(v.x), "=r"(v.y), "=r"(v.z), "=r"(v.w) : "l"(p) : "memory");
    return v;
}
__device__ __forceinline__ float lds_f(uint32_t a) { float v; asm volatile("ld.shared.f32 %0, [%1];" : "=f"(v) : "r"(a) : "memory"); return v; }
__device__ __forceinline__ uint32_t lds_u(uint32_t a) { uint32_t v; asm volatile("ld.shared.b32 %0, [%1];" : "=r"(v) : "r"(a) : "memory"); return v; }
__device__ __forceinline__ uint4 lds_u4(uint32_t a) {
    uint4 v;
    asm volatile("ld.shared.v4.b32 {%0,%1,%2,%3}, [%4];" : "=r"(v.x), "=r"(v.y), "=r"(v.z), "=r"(v.w) : "r"(a) : "memory");
    return v;
}
__device__ __forceinline__ float4 lds_f4(uint32_t a) {
    float4 v;
    asm volatile("ld.shared.v4.f32 {%0,%1,%2,%3}, [%4];" : "=f"(v.x), "=f"(v.y), "=f"(v.z), "=f"(v.w) : "r"(a) : "memory");
    return v;
}
__device__ __forceinline__ float lds_bf(uint32_t a) {
    uint16_t v;
    asm volatile("ld.shared.b16 %0, [%1];" : "=h"(v) : "r"(a) : "memory");
    return __uint_as_float((uint32_t)v << 16);
}
__device__ __forceinline__ void sts_f(uint32_t a, float v) { asm volatile("st.shared.f32 [%0], %1;" ::"r"(a), "f"(v) : "memory"); }
__device__ __forceinline__ void sts_u(uint32_t a, uint32_t v) { asm volatile("st.shared.b32 [%0], %1;" ::"r"(a), "r"(v) : "memory"); }
__device__ __forceinline__ void sts_bf(uint32_t a, float v) {
    asm volatile("st.shared.b16 [%0], %1;" ::"r"(a), "h"((uint16_t)bf16bits(v)) : "memory");
}
__device__ __forceinline__ void expect_tx(uint32_t bar, uint32_t bytes) {
    asm volatile("mbarrier.arrive.expect_tx.shared::cta.b64 _, [%0], %1;" ::"r"(bar), "r"(bytes) : "memory");
}
__device__ __forceinline__ void bulk_copy(uint32_t dst, const void* src, uint32_t bytes, uint32_t bar) {
    asm volatile("cp.async.bulk.shared::cluster.global.mbarrier::complete_tx::bytes [%0], [%1], %2, [%3];"
                 ::"r"(dst), "l"(src), "r"(bytes), "r"(bar) : "memory");
}
__device__ __forceinline__ void bulk_stream(uint32_t dst, const void* src, uint32_t bytes, uint32_t bar, uint64_t pol) {
    asm volatile("cp.async.bulk.shared::cluster.global.mbarrier::complete_tx::bytes.L2::cache_hint [%0], [%1], %2, [%3], %4;"
                 ::"r"(dst), "l"(src), "r"(bytes), "r"(bar), "l"(pol) : "memory");
}
__device__ __forceinline__ void tensor_stream(uint32_t dst, const CUtensorMap* tm, int c0, int c1, uint32_t bar, uint64_t pol) {
    asm volatile("cp.async.bulk.tensor.2d.shared::cluster.global.mbarrier::complete_tx::bytes.L2::cache_hint [%0], [%1, {%2, %3}], [%4], %5;"
                 ::"r"(dst), "l"(tm), "r"(c0), "r"(c1), "r"(bar), "l"(pol) : "memory");
}
__device__ __forceinline__ void tensor_stream_rows(uint32_t dst, const CUtensorMap* tm, int row, uint32_t bar, uint64_t pol) {
    asm volatile("cp.async.bulk.tensor.3d.shared::cluster.global.mbarrier::complete_tx::bytes.L2::cache_hint [%0], [%1, {%2, %3, %2}], [%4], %5;"
                 ::"r"(dst), "l"(tm), "r"(0), "r"(row), "r"(bar), "l"(pol) : "memory");
}
__device__ __forceinline__ void prefetch_map(const CUtensorMap* tm) { asm volatile("prefetch.tensormap [%0];" ::"l"(tm) : "memory"); }
__device__ __forceinline__ uint32_t timer_ns() { uint32_t t; asm volatile("mov.u32 %0, %%globaltimer_lo;" : "=r"(t)); return t; }
__device__ __forceinline__ void pace(uint32_t t0, int dt) {
#pragma unroll 1
    for (int it = 0; (int)(timer_ns() - t0) < dt && it < (1 << 14); it++) {}
}
__device__ __forceinline__ uint32_t next_epoch(uint32_t e) { return e + 1 < 3u * 65536u ? e + 1 : 0u; }
__device__ __forceinline__ uint32_t tagged(float v, uint32_t tag) { return (__float_as_uint(v) & ~3u) | tag; }
__device__ __forceinline__ bool has_tag(uint32_t v, uint32_t tag) { return ((v ^ tag) & 3u) == 0; }
__device__ __forceinline__ void fold_group(const float (*c)[4], float& r0, float& r1) {
    float t[8];
#pragma unroll
    for (int k = 0; k < 4; k++) {
        t[2 * k] = c[k][0] + c[k][3];
        t[2 * k + 1] = c[k][1] + c[k][2];
    }
    const float a0 = t[0] + __shfl_xor_sync(0xffffffffu, t[2], 1), a1 = t[1] + __shfl_xor_sync(0xffffffffu, t[3], 1);
    const float b0 = t[4] + __shfl_xor_sync(0xffffffffu, t[6], 1), b1 = t[5] + __shfl_xor_sync(0xffffffffu, t[7], 1);
    r0 = a0 + __shfl_xor_sync(0xffffffffu, b0, 2);
    r1 = a1 + __shfl_xor_sync(0xffffffffu, b1, 2);
}
template <typename T>
__device__ __forceinline__ T* pinned(T* p, int lane) {
    return (T*)__shfl_sync(0xffffffffu, (unsigned long long)p, lane);
}

constexpr float FIX_SCALE = 268435456.f, FIX_LIMIT = 16384.f;
constexpr unsigned long long SIDE_ARRIVAL = 129;
__device__ __forceinline__ int acc_index(int col) {
    col = (col & ~63) | ((col & 8) << 2) | ((col & 48) >> 1) | (col & 7);
    return ACC_OFF + (col >> 4 & 1) * ACC_PAIR + (col >> 5) * ACC_STEP + (col & 15);
}
__device__ __forceinline__ void fix_words(float v0, float v1, unsigned long long& w0, unsigned long long& w1) {
    constexpr uint32_t MAGIC = 0x4B400000u;
    asm volatile(
        "{\n.reg .pred p;\n.reg .f32 a0, a1, b0, b1, r0, r1;\n.reg .b32 k0, k1, i0, i1, one, lo, hi;\n"
        "abs.f32 r0, %2;\nabs.f32 r1, %3;\nsetp.lt.f32 p, r0, %4;\nsetp.lt.and.f32 p, r1, %4, p;\n"
        "fma.rn.f32 a0, %2, 0f43800000, 0f4B400000;\nfma.rn.f32 a1, %3, 0f43800000, 0f4B400000;\n"
        "sub.rn.f32 r0, a0, 0f4B400000;\nsub.rn.f32 r1, a1, 0f4B400000;\n"
        "fma.rn.f32 r0, r0, 0fBB800000, %2;\nfma.rn.f32 r1, r1, 0fBB800000, %3;\n"
        "mov.f32 b0, 0f00000000;\nmov.f32 b1, 0f00000000;\nmov.b32 k0, 0;\nmov.b32 k1, 0;\n"
        "@p fma.rn.f32 b0, r0, %5, 0f4B400000;\n@p fma.rn.f32 b1, r1, %5, 0f4B400000;\n"
        "mov.b32 i0, a0;\nmov.b32 i1, a1;\n@p mad.lo.u32 k0, i0, 4, %6;\n@p mad.lo.u32 k1, i1, 4, %6;\n"
        "selp.b32 one, 1, 0, p;\nmov.b32 i0, b0;\nmov.b32 i1, b1;\n"
        "mad.lo.u32 lo, i0, 16384, one;\nmad.hi.u32 hi, i0, 16384, k0;\nmov.b64 %0, {lo, hi};\n"
        "mad.lo.u32 lo, i1, 16384, one;\nmad.hi.u32 hi, i1, 16384, k1;\nmov.b64 %1, {lo, hi};\n}"
        : "=l"(w0), "=l"(w1) : "f"(v0), "f"(v1), "f"(FIX_LIMIT), "f"(FIX_SCALE), "n"(0u - (MAGIC * 4u + (MAGIC >> 18))));
}
__device__ __forceinline__ float fix_value(unsigned long long t) {
    constexpr float ULP = 1.0f / (16384.f * FIX_SCALE);
    return fmaf((float)(int)(t >> 32), 262144.f / FIX_SCALE, fmaf((float)(uint32_t)t, ULP, -NS * ULP));
}
__device__ __forceinline__ unsigned long long atom_add(unsigned long long* p, unsigned long long v) {
    unsigned long long old;
    asm volatile("atom.relaxed.gpu.global.add.u64 %0, [%1], %2;" : "=l"(old) : "l"(p), "l"(v) : "memory");
    return old;
}
__device__ __forceinline__ uint32_t gated_sum(float s0, float s1, uint32_t g, uint32_t x) {
    uint32_t u;
    asm("{\n.reg .b32 t;\ncvt.rn.bf16x2.f32 t, %2, %1;\nmul.rn.bf16x2 t, t, %3;\nadd.rn.bf16x2 %0, %4, t;\n}"
        : "=r"(u) : "f"(s0), "f"(s1), "r"(g), "r"(x));
    return u;
}
__device__ __forceinline__ void store_if(bool ok, uint16_t* p, uint32_t v) {
    asm volatile("{\n.reg .pred p;\nsetp.ne.b32 p, %2, 0;\n@p st.global.b16 [%0], %1;\n}" ::"l"(p), "h"((uint16_t)v), "r"((int)ok) : "memory");
}

__global__ void __launch_bounds__(NTHREADS, 1)
fused_decode_kernel(const __nv_bfloat16* __restrict__ kc, const __nv_bfloat16* __restrict__ x, Scratch* __restrict__ g,
                    __nv_bfloat16* __restrict__ out, const __grid_constant__ CUtensorMap tm_wq,
                    const __grid_constant__ CUtensorMap tm_wd, const __grid_constant__ CUtensorMap tm_wg,
                    const __grid_constant__ CUtensorMap tm_wu, const __grid_constant__ CUtensorMap tm_v,
                    const __grid_constant__ CUtensorMap tm_wo) {
    extern __shared__ __align__(1024) unsigned char smem[];
    const int tid = threadIdx.x, warp = tid >> 5, lane = tid & 31;
    asm volatile("{\n.reg .pred p;\nsetp.lt.u32 p, %1, 192;\n@p prefetch.global.L2 [%0];\n}"
                 ::"l"((const char*)kc + (size_t)((blockIdx.x >> 2) * SK + (blockIdx.x & 3) * 64) * (DH * 2) + tid * 128), "r"(tid));

    if (warp == 10) {
        const int head = blockIdx.x >> 2, part = blockIdx.x & 3;
        uint64_t pol = 0;
        const char* kp = (const char*)(kc + ((size_t)head * SK + part * 64) * DH);
        if (lane == 0) {
#pragma unroll
            for (int i = 0; i < KSLOTS; i++) mbar_init(KFULL + 8 * i, 1);
            mbar_init(XBAR, 1);
            mbar_init_fence();
            asm volatile("createpolicy.fractional.L2::evict_first.b64 %0, 1.0;" : "=l"(pol));
            expect_tx(KFULL + 8 * POS_K, KSLOT_BYTES);
            bulk_stream(SM_RING + POS_K * KSLOT_BYTES, kp, KSLOT_BYTES, KFULL + 8 * POS_K, pol);
            prefetch_map(&tm_wq);
            expect_tx(XBAR, D * 2 + 16);
            bulk_copy(SM_X, x, D * 2, XBAR);
            bulk_copy(SM_X + D * 2, g->epoch, 16, XBAR);
        }
        __syncwarp();
        bar_arrive(6, NTHREADS);
        if (lane == 0) {
            expect_tx(KFULL, 2 * WQ_BOX);
            tensor_stream(SM_RING, &tm_wq, head * DH, part * P1_ROWS, KFULL, pol);
            tensor_stream(SM_RING + WQ_BOX, &tm_wq, head * DH, part * P1_ROWS + 32, KFULL, pol);
#pragma unroll
            for (int i = 1; i < POS_K; i++) {
                expect_tx(KFULL + 8 * i, WQ_BOX);
                tensor_stream(SM_RING + i * KSLOT_BYTES, &tm_wq, head * DH, part * P1_ROWS + 32 * (i + 1), KFULL + 8 * i, pol);
            }
            prefetch_map(part < 3 ? &tm_v : &tm_wg);
            prefetch_map(part < 3 ? &tm_wo : &tm_wu);
            if (part == 3) prefetch_map(&tm_wd);
        }
        __syncwarp();
        bar_sync(7, 64);
        if (lane == 0) {
            const uint32_t t0 = timer_ns() - T_START;
            uint64_t pol_shared;
            asm volatile("createpolicy.fractional.L2::evict_normal.b64 %0, 1.0;" : "=l"(pol_shared));
#pragma unroll 1
            for (int i = POS_K + 1; i < NPOS1; i++) {
                const int s = i & (KSLOTS - 1);
                if (i >= KSLOTS) mbar_wait(KEMPTY + 8 * s, ((i >> 3) - 1) & 1);
                const int pi = i == POS_K + 1 ? 0 : i - DEPTH;
                mbar_wait(KFULL + 8 * (pi & (KSLOTS - 1)), (pi >> 3) & 1);
                pace(t0, T_K0 + T_K * (i - POS_K));
                expect_tx(KFULL + 8 * s, KSLOT_BYTES);
                bulk_stream(SM_RING + s * KSLOT_BYTES, kp + (size_t)(i - POS_K) * PARTS * KSLOT_BYTES, KSLOT_BYTES, KFULL + 8 * s, pol);
            }
            const int ntile = part < 3 ? NVT : head < NFFN ? 6 : 0, n2 = part < 3 || head >= HEAD_D0 ? ntile + 4 : ntile;
            int s = VSLOT0;
#pragma unroll 1
            for (int v = 0; v < n2; v++) {
                if (v < VSLOTS) {
                    const int k0 = s * 4 / 3;
                    mbar_wait(KEMPTY + 8 * k0, k0 >> 2);
                    mbar_wait(KEMPTY + 8 * k0 + 8, k0 >> 2);
                } else {
                    mbar_wait(VEMPTY + 8 * s, (v / VSLOTS - 1) & 1);
                }
                const int pv = v - (part == 3 ? DEPTH_F : DEPTH);
                if (pv >= 0) mbar_wait(VFULL + 8 * ((pv + VSLOT0) % VSLOTS), (pv / VSLOTS) & 1);
                else mbar_wait(KFULL + 8 * ((NPOS1 + pv) & (KSLOTS - 1)), ((NPOS1 + pv) >> 3) & 1);
                if (part < 3) pace(t0, T_V0 + (v < NVT ? T_V * v : T_V * (NVT - 1) + T_WO * (v - NVT + 1)));
                else if (v >= ntile) pace(t0, T_WD0 + T_WD * (v - ntile));
                const uint32_t full = VFULL + 8 * s, dst = SM_RING + s * VSLOT_BYTES;
                if (v >= ntile && part == 3) {
                    const int j = v - ntile;
                    expect_tx(full, DBOX);
                    tensor_stream(dst, &tm_wd, (head - HEAD_D0) * DCOLS, 2 * j * DROWS, full, pol_shared);
                    expect_tx(SFULL + 8 * j, DBOX);
                    tensor_stream(dst + DBOX, &tm_wd, (head - HEAD_D0) * DCOLS, (2 * j + 1) * DROWS, SFULL + 8 * j, pol_shared);
                } else if (v >= ntile) {
                    expect_tx(full, WO_BLK);
                    tensor_stream_rows(dst, &tm_wo, head * DH + part * CW + (v - ntile) * 16, full, pol);
                } else if (part < 3) {
                    expect_tx(full, VSLOT_BYTES);
                    tensor_stream(dst, &tm_v, part * CW, head * SK + v * 256, full, pol);
                    if (v == GATE_POS) {
                        expect_tx(XBAR, D * 4);
                        bulk_copy(SM_S, g->xg, D * 4, XBAR);
                    }
                    const int st = (v + 1) >> 2;
                    if (v == 0 || ((v & 3) == 3 && st < 4)) {
                        expect_tx(SFULL + 8 * st, 4096);
                        bulk_copy(SM_S + st * 4096, g->xs + head * SK + st * 1024, 4096, SFULL + 8 * st);
                    }
                } else {
                    const int t = v < 3 ? v : v - 3;
                    const CUtensorMap* tm = v < 3 ? &tm_wg : &tm_wu;
                    expect_tx(full, t < 2 ? VSLOT_BYTES : VSLOT_BYTES / 2);
                    tensor_stream(dst, tm, head * CW, t * 256, full, pol);
                    if (t < 2) tensor_stream(dst + VSLOT_BYTES / 2, tm, head * CW, t * 256 + 128, full, pol);
                }
                s = s == VSLOTS - 1 ? 0 : s + 1;
            }
        }
        return;
    }

    const int cta = __shfl_sync(0xffffffffu, (int)blockIdx.x, 0), head = cta >> 2, part = cta & 3;

    const int n = lane >> 2, t4 = lane & 3, n0 = t4 * 2, r8 = lane & 7;
    const bool is_hi = n == n0 + 1, diag = n == n0 || is_hi;
    const int dsh = is_hi ? 16 : 0;
    uint32_t offv[4];
#pragma unroll
    for (int i = 0; i < 4; i++) offv[i] = (uint32_t)(((2 * i + ((lane >> 3) & 1)) ^ r8) * 16);
    const int keyv = r8 + 8 * (lane >> 4);
    const uint32_t red = SM_RED + warp * RED_STRIDE;

    if (warp == 9) {
        if (lane == 0) {
#pragma unroll
            for (int i = 0; i < KSLOTS; i++) mbar_init(KEMPTY + 8 * i, 8);
#pragma unroll
            for (int i = 0; i < VSLOTS; i++) {
                mbar_init(VFULL + 8 * i, 1);
                mbar_init(VEMPTY + 8 * i, 8);
            }
#pragma unroll
            for (int i = 0; i < 4; i++) mbar_init(SFULL + 8 * i, 1);
            mbar_init(OBAR, 2);
            mbar_init_fence();
        }
        __syncwarp();
        bar_arrive(7, 64);
    }
    float* const xq = g->xq + head * PARTS * DH + tid;
    if (warp < 6) st_rlx(xq + part * DH, 0u);
    bar_sync(6, NTHREADS);
    mbar_wait(XBAR, 0);
    const uint32_t epoch = next_epoch(lds_u(SM_X + D * 2));
    const uint32_t tag = epoch % 3u + 1u, tag16 = epoch & 0xffffu;

    float ln_m, ln_d;
    {
        float v[20];
#pragma unroll
        for (int i = 0; i < 10; i++) {
            const uint32_t u = lds_u(SM_X + (lane + 32 * i) * 4);
            v[2 * i] = __uint_as_float(u << 16);
            v[2 * i + 1] = __uint_as_float(u & 0xffff0000u);
        }
        float sum = 0.f, sq = 0.f;
#pragma unroll
        for (int i = 0; i < 20; i++) sum += v[i];
#pragma unroll
        for (int o = 16; o; o >>= 1) sum += __shfl_xor_sync(0xffffffffu, sum, o);
        const float mean = sum * (1.0f / D);
#pragma unroll
        for (int i = 0; i < 20; i++) sq = fmaf(v[i] - mean, v[i] - mean, sq);
#pragma unroll
        for (int o = 16; o; o >>= 1) sq += __shfl_xor_sync(0xffffffffu, sq, o);
        ln_m = bf16r(mean);
        ln_d = bf16r(__fsqrt_rn(bf16r(bf16r(sq * (1.0f / D)) + 1e-5f)));
    }
    auto xn = [&](float xv) -> float { return __fdividef(bf16r(xv - ln_m), ln_d); };

    {
        const uint32_t xr = SM_X + (part * P1_ROWS + warp * 16 + n) * 2;
        const uint32_t b0 = diag ? bf16bits(xn(lds_bf(xr))) << dsh : 0u, b1 = diag ? bf16bits(xn(lds_bf(xr + 16))) << dsh : 0u;
        const int s = warp < 4 ? 0 : (warp >> 1) - 1;
        mbar_wait(KFULL + 8 * s, 0);
        const uint32_t base = SM_RING + s * KSLOT_BYTES + ((warp < 4 ? warp : warp & 1) * 16 + keyv) * (DH * 2);
        float c[12][4];
#pragma unroll
        for (int i = 0; i < 12; i++) {
            uint32_t a[4];
            c[i][0] = c[i][1] = c[i][2] = c[i][3] = 0.f;
            ldsm4t(a, base + (i >> 2) * 128 + offv[i & 3]);
            mma16816(c[i], a, b0, b1);
        }
        __syncwarp();
        if (lane < (warp < 4 ? 2 : 4)) mbar_arrive(KEMPTY + 8 * s);
#pragma unroll
        for (int j = 0; j < 3; j++) {
            float r0, r1;
            fold_group(c + 4 * j, r0, r1);
            sts_f(red + ((j * 8 + n0) * 8 + n) * 4, r0);
            sts_f(red + ((j * 8 + n0 + 1) * 8 + n) * 4, r1);
        }
    }

    const bool gemv = part < 3 || head < NFFN;
    const int n4 = part < 3 ? 320 : 256;
    if (warp < 8) {
        if (warp < 6) {
            bar_sync(1, 320);
            float s = 0.f;
#pragma unroll
            for (int w = 0; w < 10; w++) s += lds_f(SM_RED + w * RED_STRIDE + tid * 4);
            const uint32_t own = tagged(s, tag);
            st_rlx(xq + part * DH, own);
            const uint32_t tg = next_epoch(lds_u(SM_X + D * 2)) % 3u + 1u;
            uint32_t pv[PARTS];
#pragma unroll
            for (int j = 0; j < PARTS; j++) pv[j] = j == part ? own : 0u;
#pragma unroll 1
            for (int it = 0;; it++) {
                if (has_tag(pv[0], tg) && has_tag(pv[1], tg) && has_tag(pv[2], tg) && has_tag(pv[3], tg)) break;
                if (it == SPIN_LIMIT) __trap();
                if (it) __nanosleep(100);
#pragma unroll
                for (int j = 0; j < PARTS; j++)
                    if (!has_tag(pv[j], tg)) pv[j] = ld_rlx(xq + j * DH);
            }
            sts_bf(SM_Q + tid * 2, (__uint_as_float(pv[0]) + __uint_as_float(pv[1])) + (__uint_as_float(pv[2]) + __uint_as_float(pv[3])));
        } else {
            bar_arrive(1, 320);
        }
        bar_sync(2, 256);

        {
            const int grp = warp >> 2;
            uint32_t qb[12][2], offk[4];
#pragma unroll
            for (int i = 0; i < 12; i++)
#pragma unroll
                for (int e = 0; e < 2; e++) qb[i][e] = lds_u(SM_Q + (((i >> 2) * 8 + ((2 * (i & 3) + e) ^ n)) * 8 + n0) * 2);
#pragma unroll
            for (int i = 0; i < 4; i++) offk[i] = (uint32_t)(((2 * i + (lane >> 4)) ^ r8) * 16);
            const uint32_t rowk = SM_RING + ((warp & 3) * 16 + r8 + 8 * ((lane >> 3) & 1)) * (DH * 2);
            uint32_t* xs_out = g->xs + head * SK + (grp * PARTS + part) * 64 + (warp & 3) * 16 + n;
#pragma unroll 1
            for (int u = 0; u < NKT / 2; u++) {
                const int i = POS_K + 2 * u + grp, s = i & (KSLOTS - 1);
                mbar_wait(KFULL + 8 * s, (i >> 3) & 1);
                const uint32_t base = rowk + s * KSLOT_BYTES;
                float c[3][4];
#pragma unroll
                for (int j = 0; j < 3; j++) c[j][0] = c[j][1] = c[j][2] = c[j][3] = 0.f;
#pragma unroll
                for (int k = 0; k < 4; k++)
#pragma unroll
                    for (int j = 0; j < 3; j++) {
                        uint32_t a[4];
                        ldsm4(a, base + j * 128 + offk[k]);
                        mma16816(c[j], a, qb[j * 4 + k][0], qb[j * 4 + k][1]);
                    }
                __syncwarp();
                if (lane < 2) mbar_arrive(KEMPTY + 8 * s);
                const float d0 = is_hi ? c[0][1] + c[1][1] + c[2][1] : c[0][0] + c[1][0] + c[2][0];
                const float d1 = is_hi ? c[0][3] + c[1][3] + c[2][3] : c[0][2] + c[1][2] + c[2][2];
                if (diag) {
                    st_rlx(xs_out, (bf16bits(bf16r(d0) * SCORE_SCALE) << 16) | tag16);
                    st_rlx(xs_out + 8, (bf16bits(bf16r(d1) * SCORE_SCALE) << 16) | tag16);
                }
                xs_out += 2 * PARTS * 64;
            }
        }

        const uint32_t rowv = SM_RING + keyv * 128;
        int s = VSLOT0, ph = 0;
        if (part < 3) {
            float acc[4][4], m = -INFINITY, l = 0.f, scale = 0.f;
#pragma unroll
            for (int k = 0; k < 4; k++) acc[k][0] = acc[k][1] = acc[k][2] = acc[k][3] = 0.f;
            const uint32_t pw = SM_P + warp * 256;
            const uint32_t pst = pw + ((lane >> 3) * 16 + (lane & 1) * 8 + ((lane >> 2) & 1) * 2 + ((lane >> 1) & 1)) * 4;
#pragma unroll 1
            for (int st = 0; st < 4; st++) {
                const int key0 = st * 1024 + (lane >> 3) * 256 + warp * 32 + r8 * 4;
                mbar_wait(SFULL + 8 * st, 0);
                uint4 sc = lds_u4(SM_S + key0 * 4);
#pragma unroll 1
                for (int it = 0;; it++) {
                    if (((((sc.x ^ tag16) | (sc.y ^ tag16)) | ((sc.z ^ tag16) | (sc.w ^ tag16))) & 0xffffu) == 0) break;
                    if (it == SPIN_LIMIT) __trap();
                    if (it) __nanosleep(100);
                    sc = ld_rlx4(g->xs + head * SK + key0);
                }
                const float s0 = __uint_as_float(sc.x & 0xffff0000u), s1 = __uint_as_float(sc.y & 0xffff0000u);
                const float s2 = __uint_as_float(sc.z & 0xffff0000u), s3 = __uint_as_float(sc.w & 0xffff0000u);
                __syncwarp();
                float mn = fmaxf(fmaxf(s0, s1), fmaxf(s2, s3));
#pragma unroll
                for (int o = 16; o; o >>= 1) mn = fmaxf(mn, __shfl_xor_sync(0xffffffffu, mn, o));
                mn = fmaxf(mn, m);
                const float f = exp2f((m - mn) * LOG2E);
                m = mn;
                const float p0 = exp2f((s0 - m) * LOG2E), p1 = exp2f((s1 - m) * LOG2E);
                const float p2 = exp2f((s2 - m) * LOG2E), p3 = exp2f((s3 - m) * LOG2E);
                l = l * f + ((p0 + p1) + (p2 + p3));
#pragma unroll
                for (int k = 0; k < 4; k++) { acc[k][0] *= f; acc[k][2] *= f; }
                sts_u(pst, pack2(p0, p1));
                sts_u(pst + 16, pack2(p2, p3));
                __syncwarp();
                if (st == 3) {
#pragma unroll
                    for (int o = 16; o; o >>= 1) l += __shfl_xor_sync(0xffffffffu, l, o);
                    if (lane == 0) { sts_f(SM_MISC + warp * 4, m); sts_f(SM_MISC + 32 + warp * 4, l); }
                    bar_sync(3, 256);
                    const float mw = lds_f(SM_MISC + r8 * 4), lw = lds_f(SM_MISC + 32 + r8 * 4);
                    float mm = mw;
#pragma unroll
                    for (int o = 4; o; o >>= 1) mm = fmaxf(mm, __shfl_xor_sync(0xffffffffu, mm, o));
                    float ls = lw * exp2f((mw - mm) * LOG2E);
#pragma unroll
                    for (int o = 4; o; o >>= 1) ls += __shfl_xor_sync(0xffffffffu, ls, o);
                    scale = __fdividef(exp2f((m - mm) * LOG2E), ls);
                }
#pragma unroll 1
                for (int u = 0; u < 4; u++) {
                    const uint4 pb = lds_u4(pw + u * 64 + t4 * 16);
                    mbar_wait(VFULL + 8 * s, ph);
                    const uint32_t base = rowv + s * VSLOT_BYTES + warp * 32 * 128;
                    uint32_t a[8][4];
#pragma unroll
                    for (int k = 0; k < 8; k++) ldsm4t(a[k], base + (k >> 2) * 2048 + offv[k & 3]);
#pragma unroll
                    for (int k = 0; k < 8; k++) mma16816(acc[k & 3], a[k], k < 4 ? pb.x : pb.z, k < 4 ? pb.y : pb.w);
                    __syncwarp();
                    if (lane == 0) mbar_arrive(VEMPTY + 8 * s);
                    if (++s == VSLOTS) s = 0;
                    if (s == VSLOT0) ph ^= 1;
                }
            }
            const float o0 = t4 == 0 ? acc[0][0] : t4 == 1 ? acc[1][0] : t4 == 2 ? acc[2][0] : acc[3][0];
            const float o1 = t4 == 0 ? acc[0][2] : t4 == 1 ? acc[1][2] : t4 == 2 ? acc[2][2] : acc[3][2];
            sts_f(SM_RED + ((t4 * 16 + n) * 8 + (warp ^ t4)) * 4, o0 * scale);
            sts_f(SM_RED + ((t4 * 16 + 8 + n) * 8 + (warp ^ t4)) * 4, o1 * scale);
        } else if (gemv) {
#pragma unroll 1
            for (int mat = 0; mat < 2; mat++) {
                float acc[4][4];
#pragma unroll
                for (int k = 0; k < 4; k++) acc[k][0] = acc[k][1] = acc[k][2] = acc[k][3] = 0.f;
#pragma unroll 1
                for (int t = 0; t < 3; t++) {
                    mbar_wait(VFULL + 8 * s, 0);
#pragma unroll 1
                    for (int ks = 0; ks < (t < 2 ? 2 : 1); ks++) {
                        const int row = t < 2 ? warp * 32 + ks * 16 : warp * 16;
                        const uint32_t u0 = lds_u(SM_X + (t * 256 + row + n0) * 2), u1 = lds_u(SM_X + (t * 256 + row + 8 + n0) * 2);
                        const uint32_t b0 = pack2(xn(__uint_as_float(u0 << 16)), xn(__uint_as_float(u0 & 0xffff0000u)));
                        const uint32_t b1 = pack2(xn(__uint_as_float(u1 << 16)), xn(__uint_as_float(u1 & 0xffff0000u)));
#pragma unroll
                        for (int k = 0; k < 4; k++) {
                            uint32_t a[4];
                            ldsm4t(a, rowv + s * VSLOT_BYTES + row * 128 + offv[k]);
                            mma16816(acc[k], a, b0, b1);
                        }
                    }
                    __syncwarp();
                    if (lane == 0) mbar_arrive(VEMPTY + 8 * s);
                    if (++s == VSLOTS) s = 0;
                }
                const float o0 = t4 == 0 ? acc[0][0] : t4 == 1 ? acc[1][0] : t4 == 2 ? acc[2][0] : acc[3][0];
                const float o1 = t4 == 0 ? acc[0][2] : t4 == 1 ? acc[1][2] : t4 == 2 ? acc[2][2] : acc[3][2];
                sts_f(SM_RED + mat * 2048 + ((t4 * 16 + n) * 8 + (warp ^ t4)) * 4, o0);
                sts_f(SM_RED + mat * 2048 + ((t4 * 16 + 8 + n) * 8 + (warp ^ t4)) * 4, o1);
            }
        }
        if (gemv) {
            if (warp < 2) {
                bar_sync(4, n4);
                const float4 a0 = lds_f4(SM_RED + tid * 32), a1 = lds_f4(SM_RED + tid * 32 + 16);
                float r = ((a0.x + a0.y) + (a0.z + a0.w)) + ((a1.x + a1.y) + (a1.z + a1.w));
                if (part == 3) {
                    const float4 u0 = lds_f4(SM_RED + 2048 + tid * 32), u1 = lds_f4(SM_RED + 2048 + tid * 32 + 16);
                    r = bf16r(silu(bf16r(r))) * bf16r(((u0.x + u0.y) + (u0.z + u0.w)) + ((u1.x + u1.y) + (u1.z + u1.w)));
                    st_rlx(g->xh + head * CW + tid, (bf16bits(r) << 16) | tag16);
                } else {
                    sts_bf(SM_O + ((tid >> 1) & 3) * 32 + (tid >> 3) * 4 + (tid & 1) * 2, r);
                    __syncwarp();
                    if (lane == 0) mbar_arrive(OBAR);
                }
            } else {
                bar_arrive(4, n4);
            }
        }
    } else {
        bar_arrive(1, 320);
        if ((uint32_t)__cvta_generic_to_shared(smem) != SB) __trap();
        if (part < 3) bar_sync(4, 320);
    }

    if (part < 3) {
        const uint32_t roww = SM_RING + keyv * 128 + warp * 2048;
        const int col = (warp * 8 + n0) * 8 + n;
        mbar_wait(XBAR, 1);
        uint32_t g0 = lds_u(SM_S + col * 4), g1 = lds_u(SM_S + col * 4 + 32);
#pragma unroll 1
        for (int it = 0; (((g0 ^ tag16) | (g1 ^ tag16)) & 0xffffu) != 0; it++) {
            if (it == SPIN_LIMIT) __trap();
            g0 = ld_rlx(g->xg + col);
            g1 = ld_rlx(g->xg + col + 8);
        }
        __syncwarp();
        const float x0 = lds_bf(SM_X + col * 2), x1 = lds_bf(SM_X + col * 2 + 16);
        const uint32_t gp = __byte_perm(g0, g1, 0x7632), xp = __byte_perm(__float_as_uint(x0), __float_as_uint(x1), 0x7632);
        unsigned long long* const acc = pinned(g->acc + acc_index(col), lane);
        uint16_t* const outp = pinned((uint16_t*)out + col, lane);
        mbar_wait(OBAR, 0);
        const uint4 u0 = lds_u4(SM_O + t4 * 32), u1 = lds_u4(SM_O + t4 * 32 + 16);
        const uint32_t bo[4][2] = {{u0.x, u0.y}, {u0.z, u0.w}, {u1.x, u1.y}, {u1.z, u1.w}};
        float c[4][4];
#pragma unroll
        for (int k = 0; k < 4; k++) c[k][0] = c[k][1] = c[k][2] = c[k][3] = 0.f;
#pragma unroll
        for (int ks = 0; ks < 4; ks++) {
            const int s = (NVT + ks + VSLOT0) % VSLOTS;
            if (ks < 3) mbar_wait(VFULL + 8 * s, ((NVT + ks) / VSLOTS) & 1);
            else mbar_spin(VFULL + 8 * s, ((NVT + ks) / VSLOTS) & 1);
            uint32_t a[4][4];
#pragma unroll
            for (int k = 0; k < 4; k++) ldsm4t(a[k], roww + offv[k] + s * VSLOT_BYTES);
#pragma unroll
            for (int k = 3; k >= 0; k--) mma16816(c[k], a[k], bo[ks][0], bo[ks][1]);
        }
        const float r0 = t4 & 2 ? (t4 & 1 ? c[3][0] : c[2][0]) : (t4 & 1 ? c[1][0] : c[0][0]);
        const float r1 = t4 & 2 ? (t4 & 1 ? c[3][2] : c[2][2]) : (t4 & 1 ? c[1][2] : c[0][2]);
        unsigned long long w0, w1;
        fix_words(r0, r1, w0, w1);
        const bool in_range = (uint32_t)w0 & 1u;
        unsigned long long t0 = atom_add(acc, w0) + w0, t1 = atom_add(acc + ACC_STEP, w1) + w1;
        uint32_t u = gated_sum(fix_value(t0), fix_value(t1), gp, xp);
        store_if(((uint32_t)t0 & 0x3fffu) == NS, outp, u);
        store_if(((uint32_t)t1 & 0x3fffu) == NS, outp + 8, u >> 16);
        if (!in_range | ((((uint32_t)t0 | (uint32_t)t1) & (127u << 7)) != 0)) {
            if (!in_range) {
                atomicAdd(g->big + col, r0);
                atomicAdd(g->big + col + 8, r1);
                __threadfence();
                t0 = atom_add(acc, SIDE_ARRIVAL) + SIDE_ARRIVAL;
                t1 = atom_add(acc + ACC_STEP, SIDE_ARRIVAL) + SIDE_ARRIVAL;
            }
            __threadfence();
            u = gated_sum(fix_value(t0) + __uint_as_float(ld_rlx(g->big + col)), fix_value(t1) + __uint_as_float(ld_rlx(g->big + col + 8)), gp, xp);
            store_if(((uint32_t)t0 & 127u) == NS, outp, u);
            store_if(((uint32_t)t1 & 127u) == NS, outp + 8, u >> 16);
        }
        if (col == 0 && ((uint32_t)t0 & 127u) == NS) st_rlx(g->epoch, epoch);
    }

    if (part == 3 && head >= HEAD_D0) {
        if (warp < 6) {
            const uint32_t* src = g->xh + tid * 8;
            uint4 h0, h1;
#pragma unroll 1
            for (int it = 0;; it++) {
                h0 = ld_rlx4(src);
                h1 = ld_rlx4(src + 4);
                const uint32_t bad = ((h0.x ^ tag16) | (h0.y ^ tag16)) | ((h0.z ^ tag16) | (h0.w ^ tag16)) |
                                     ((h1.x ^ tag16) | (h1.y ^ tag16)) | ((h1.z ^ tag16) | (h1.w ^ tag16));
                if ((bad & 0xffffu) == 0) break;
                if (it == SPIN_LIMIT) __trap();
                __nanosleep(500);
            }
            const uint32_t hs = SM_S + (tid >> 2) * 64 + (tid & 3) * 4;
            sts_u(hs, __byte_perm(h0.x, h0.y, 0x7632));
            sts_u(hs + 16, __byte_perm(h0.z, h0.w, 0x7632));
            sts_u(hs + 32, __byte_perm(h1.x, h1.y, 0x7632));
            sts_u(hs + 48, __byte_perm(h1.z, h1.w, 0x7632));
            bar_sync(3, 192);
            uint4 hb[8];
#pragma unroll
            for (int b = 0; b < 8; b++) hb[b] = lds_u4(SM_S + (b * 6 + warp) * 64 + t4 * 16);
            const uint32_t ph = head < NFFN ? 1 : 0;
            const uint32_t rowd = SM_RING + (warp * 32 + keyv) * 64;
            const uint32_t c0 = (((lane >> 3) & 1) ^ (r8 >> 1)) * 16, c1 = c0 ^ 32;
            float c[4][4];
#pragma unroll
            for (int k = 0; k < 4; k++) c[k][0] = c[k][1] = c[k][2] = c[k][3] = 0.f;
            uint32_t a[2][4][4];
#pragma unroll
            for (int b = 0; b <= 8; b++) {
                if (b < 8) {
                    const int s = (VSLOT0 + (b >> 1)) % VSLOTS;
                    if (b & 1) mbar_wait(SFULL + 8 * (b >> 1), 0);
                    else mbar_wait(VFULL + 8 * s, ph);
                    const uint32_t base = rowd + s * VSLOT_BYTES + (b & 1) * DBOX;
                    ldsm4t(a[b & 1][0], base + c0);
                    ldsm4t(a[b & 1][1], base + c1);
                    ldsm4t(a[b & 1][2], base + 1024 + c0);
                    ldsm4t(a[b & 1][3], base + 1024 + c1);
                }
                if (b > 0) {
                    const uint4 hv = hb[b - 1];
                    mma16816(c[0], a[~b & 1][0], hv.x, hv.y);
                    mma16816(c[1], a[~b & 1][1], hv.x, hv.y);
                    mma16816(c[2], a[~b & 1][2], hv.z, hv.w);
                    mma16816(c[3], a[~b & 1][3], hv.z, hv.w);
                }
            }
            const float f = t4 == 0 ? c[0][0] + c[2][0] : t4 == 1 ? c[0][2] + c[2][2] : t4 == 2 ? c[1][0] + c[3][0] : c[1][2] + c[3][2];
            sts_f(SM_P + warp * 128 + (t4 * 8 + n) * 4, f);
            bar_arrive(5, 224);
        } else if (warp == 8) {
            const int col = (head - HEAD_D0) * DCOLS + lane;
            asm volatile("st.relaxed.gpu.global.u64 [%0], %1;" ::"l"(g->acc + acc_index(col)), "l"(0ull) : "memory");
            st_rlx(g->big + col, 0u);
            __threadfence();
            bar_sync(5, 224);
            float t = 0.f;
#pragma unroll
            for (int w = 0; w < 6; w++) t += lds_f(SM_P + w * 128 + lane * 4);
            st_rlx(g->xg + col, (bf16bits(silu(bf16r(t))) << 16) | tag16);
        }
    }
}

typedef CUresult (*EncodeFn)(CUtensorMap*, CUtensorMapDataType, cuuint32_t, void*, const cuuint64_t*, const cuuint64_t*,
                             const cuuint32_t*, const cuuint32_t*, CUtensorMapInterleave, CUtensorMapSwizzle,
                             CUtensorMapL2promotion, CUtensorMapFloatOOBfill);

void encode_map(EncodeFn fn, CUtensorMap* tm, void* base, int cols, int rows, int box_cols, int box_rows,
                CUtensorMapSwizzle swz, int groups = 1) {
    const cuuint64_t dims[3] = {(cuuint64_t)(cols / groups), (cuuint64_t)rows, (cuuint64_t)groups};
    const cuuint64_t strides[2] = {(cuuint64_t)cols * 2, (cuuint64_t)(cols / groups) * 2};
    const cuuint32_t box[3] = {(cuuint32_t)box_cols, (cuuint32_t)box_rows, (cuuint32_t)groups};
    const cuuint32_t estr[3] = {1, 1, 1};
    fn(tm, CU_TENSOR_MAP_DATA_TYPE_BFLOAT16, groups > 1 ? 3 : 2, base, dims, strides, box, estr, CU_TENSOR_MAP_INTERLEAVE_NONE,
       swz, CU_TENSOR_MAP_L2_PROMOTION_L2_128B, CU_TENSOR_MAP_FLOAT_OOB_FILL_NONE);
}

}

extern "C" void kernel_launch(void* const* d_in, const int* in_sizes, int n_in, void* d_out, int out_size) {
    static EncodeFn encode = nullptr;
    static Scratch* scratch = nullptr;
    if (!encode) {
        cudaDriverEntryPointQueryResult qr;
        cudaGetDriverEntryPoint("cuTensorMapEncodeTiled", (void**)&encode, cudaEnableDefault, &qr);
        void* raw;
        cudaGetSymbolAddress(&raw, g_scratch);
        scratch = (Scratch*)(((uintptr_t)raw + SCRATCH_ALIGN - 1) & ~(uintptr_t)(SCRATCH_ALIGN - 1));
        cudaFuncSetAttribute(fused_decode_kernel, cudaFuncAttributeMaxDynamicSharedMemorySize, SMEM_BYTES);
    }
    CUtensorMap tm_wq, tm_wd, tm_wg, tm_wu, tm_v, tm_wo;
    encode_map(encode, &tm_wq, d_in[3], H * DH, D, DH, 32, CU_TENSOR_MAP_SWIZZLE_NONE);
    encode_map(encode, &tm_wd, d_in[8], D, F, DCOLS, DROWS, CU_TENSOR_MAP_SWIZZLE_64B);
    encode_map(encode, &tm_wg, d_in[6], F, D, CW, 128, CU_TENSOR_MAP_SWIZZLE_128B);
    encode_map(encode, &tm_wu, d_in[7], F, D, CW, 128, CU_TENSOR_MAP_SWIZZLE_128B);
    encode_map(encode, &tm_v, d_in[2], DH, H * SK, CW, 256, CU_TENSOR_MAP_SWIZZLE_128B);
    encode_map(encode, &tm_wo, d_in[4], D, H * DH, CW, 16, CU_TENSOR_MAP_SWIZZLE_128B, D / CW);
    fused_decode_kernel<<<NCTA, NTHREADS, SMEM_BYTES, cudaStreamPerThread>>>(
        (const __nv_bfloat16*)d_in[1], (const __nv_bfloat16*)d_in[0], scratch, (__nv_bfloat16*)d_out, tm_wq, tm_wd, tm_wg,
        tm_wu, tm_v, tm_wo);
}
```

```cpp
#include <cuda.h>
#include <cuda_runtime.h>
#include <cuda_bf16.h>
#include <stdint.h>

namespace {

constexpr int D = 640, H = 32, DH = 192, SK = 4096, F = 1536;
constexpr int PARTS = 4, NCTA = H * PARTS, NTHREADS = 352;
constexpr int KSLOTS = 8, KSLOT_BYTES = 24576;
constexpr int VSLOTS = 6, VSLOT_BYTES = 32768;
constexpr int NKT = 16, NVT = 16;
constexpr int POS_K = 4, NPOS1 = POS_K + NKT;
constexpr int VSLOT0 = 3;
constexpr int CW = 64;
constexpr int WO_BLK = 16 * D * 2;
constexpr int WO_PIECES = 5, WO_PIECE = WO_BLK / WO_PIECES;
constexpr int NFFN = F / CW;
constexpr int NS = H * 3;
constexpr int P1_ROWS = D / PARTS;
constexpr int WQ_BOX = 32 * DH * 2;
constexpr int DCOLS = 32, DROWS = 192;
constexpr int DBOX = DCOLS * DROWS * 2;
constexpr int HEAD_D0 = H - D / DCOLS;
constexpr int SPIN_LIMIT = 1 << 20;
constexpr uint32_t WAIT_CLOCKS = 1u << 30;
constexpr float LOG2E = 1.4426950408889634f, SCORE_SCALE = 0.07216878364870322f;

constexpr int T_START = 650;
constexpr int T_K0 = 1000, T_K = 1000, T_V0 = 17200, T_V = 1095, T_WO = 610, T_WD0 = 23500, T_WD = 1400;
constexpr int DEPTH = 4, DEPTH_F = 6;
constexpr int GATE_POS = 15;

constexpr uint32_t SB = 1024;
constexpr uint32_t SM_RING = SB;
constexpr uint32_t SM_S = SM_RING + KSLOTS * KSLOT_BYTES;
constexpr uint32_t SM_X = SM_S + SK * 4;
constexpr uint32_t SM_RED = SM_X + 1408;
constexpr uint32_t RED_STRIDE = DH * 4;
constexpr uint32_t SM_P = SM_RED + 10 * RED_STRIDE;
constexpr uint32_t SM_Q = SM_P + 8 * 256;
constexpr uint32_t SM_O = SM_Q + DH * 2;
constexpr uint32_t SM_MISC = SM_O + CW * 4;
constexpr uint32_t KFULL = SM_MISC + 64, KEMPTY = KFULL + 8 * KSLOTS, VFULL = KEMPTY + 8 * KSLOTS,
                   VEMPTY = VFULL + 8 * VSLOTS, XBAR = VEMPTY + 8 * VSLOTS, SFULL = XBAR + 8, OBAR = SFULL + 32,
                   LFULL = OBAR + 8;
constexpr int SMEM_BYTES = LFULL + 8 * WO_PIECES - SB;

constexpr size_t SCRATCH_ALIGN = 1 << 18;
constexpr int ACC_OFF = 32, ACC_PAIR = 96, ACC_STEP = 512;
struct __align__(128) Scratch {
    unsigned long long acc[D / 32 * ACC_STEP + 512];
    unsigned epoch[128];
    float xq[NCTA * DH];
    uint32_t xs[H * SK];
    uint32_t xh[F];
    uint32_t xg[D];
    float big[D];
};
__device__ __align__(128) unsigned char g_scratch[sizeof(Scratch) + SCRATCH_ALIGN];

__device__ __forceinline__ void mbar_init(uint32_t bar, uint32_t cnt) {
    asm volatile("mbarrier.init.shared::cta.b64 [%0], %1;" ::"r"(bar), "r"(cnt) : "memory");
}
__device__ __forceinline__ void mbar_init_fence() {
    asm volatile("fence.mbarrier_init.release.cluster;" ::: "memory");
    asm volatile("fence.proxy.async.shared::cta;" ::: "memory");
}
__device__ __forceinline__ void mbar_arrive(uint32_t bar) {
    asm volatile("mbarrier.arrive.shared::cta.b64 _, [%0];" ::"r"(bar) : "memory");
}
__device__ __forceinline__ bool mbar_try(uint32_t bar, uint32_t parity) {
    uint32_t ok;
    asm volatile("{\n.reg .pred p;\nmbarrier.try_wait.parity.shared::cta.b64 p, [%1], %2;\nselp.u32 %0, 1, 0, p;\n}"
                 : "=r"(ok) : "r"(bar), "r"(parity) : "memory");
    return ok;
}
__device__ __forceinline__ bool mbar_test(uint32_t bar, uint32_t parity) {
    uint32_t ok;
    asm volatile("{\n.reg .pred p;\nmbarrier.test_wait.parity.shared::cta.b64 p, [%1], %2;\nselp.u32 %0, 1, 0, p;\n}"
                 : "=r"(ok) : "r"(bar), "r"(parity) : "memory");
    return ok;
}
__device__ __forceinline__ void mbar_wait(uint32_t bar, uint32_t parity) {
    if (mbar_try(bar, parity)) return;
    const uint32_t t0 = (uint32_t)clock();
#pragma unroll 1
    while (!mbar_try(bar, parity))
        if ((uint32_t)clock() - t0 > WAIT_CLOCKS) __trap();
}
__device__ __forceinline__ void mbar_spin(uint32_t bar, uint32_t parity) {
#pragma unroll 1
    for (uint32_t it = 0; !mbar_test(bar, parity); it++)
        if (it > (1u << 26)) __trap();
}
__device__ __forceinline__ void bar_sync(int id, int n) { asm volatile("bar.sync %0, %1;" ::"r"(id), "r"(n) : "memory"); }
__device__ __forceinline__ void bar_arrive(int id, int n) { asm volatile("bar.arrive %0, %1;" ::"r"(id), "r"(n) : "memory"); }
__device__ __forceinline__ void ldsm4(uint32_t (&a)[4], uint32_t addr) {
    asm volatile("ldmatrix.sync.aligned.m8n8.x4.shared.b16 {%0,%1,%2,%3}, [%4];"
                 : "=r"(a[0]), "=r"(a[1]), "=r"(a[2]), "=r"(a[3]) : "r"(addr) : "memory");
}
__device__ __forceinline__ void ldsm4t(uint32_t (&a)[4], uint32_t addr) {
    asm volatile("ldmatrix.sync.aligned.m8n8.x4.trans.shared.b16 {%0,%1,%2,%3}, [%4];"
                 : "=r"(a[0]), "=r"(a[1]), "=r"(a[2]), "=r"(a[3]) : "r"(addr) : "memory");
}
__device__ __forceinline__ void mma16816(float (&c)[4], const uint32_t (&a)[4], uint32_t b0, uint32_t b1) {
    asm volatile("mma.sync.aligned.m16n8k16.row.col.f32.bf16.bf16.f32 {%0,%1,%2,%3}, {%4,%5,%6,%7}, {%8,%9}, {%0,%1,%2,%3};"
                 : "+f"(c[0]), "+f"(c[1]), "+f"(c[2]), "+f"(c[3])
                 : "r"(a[0]), "r"(a[1]), "r"(a[2]), "r"(a[3]), "r"(b0), "r"(b1));
}
__device__ __forceinline__ float bf16r(float v) { return __bfloat162float(__float2bfloat16_rn(v)); }
__device__ __forceinline__ uint32_t bf16bits(float v) { return (uint32_t)__bfloat16_as_ushort(__float2bfloat16_rn(v)); }
__device__ __forceinline__ uint32_t pack2(float lo, float hi) {
    uint32_t r;
    asm("cvt.rn.bf16x2.f32 %0, %1, %2;" : "=r"(r) : "f"(hi), "f"(lo));
    return r;
}
__device__ __forceinline__ float silu(float v) { return __fdividef(v, 1.0f + __expf(-v)); }
__device__ __forceinline__ void st_rlx(void* p, uint32_t v) {
    asm volatile("st.relaxed.gpu.global.b32 [%0], %1;" ::"l"(p), "r"(v) : "memory");
}
__device__ __forceinline__ uint32_t ld_rlx(const void* p) {
    uint32_t v;
    asm volatile("ld.relaxed.gpu.global.b32 %0, [%1];" : "=r"(v) : "l"(p) : "memory");
    return v;
}
__device__ __forceinline__ uint4 ld_rlx4(const void* p) {
    uint4 v;
    asm volatile("ld.relaxed.gpu.global.v4.b32 {%0,%1,%2,%3}, [%4];" : "=r"(v.x), "=r"(v.y), "=r"(v.z), "=r"(v.w) : "l"(p) : "memory");
    return v;
}
__device__ __forceinline__ float lds_f(uint32_t a) { float v; asm volatile("ld.shared.f32 %0, [%1];" : "=f"(v) : "r"(a) : "memory"); return v; }
__device__ __forceinline__ uint32_t lds_u(uint32_t a) { uint32_t v; asm volatile("ld.shared.b32 %0, [%1];" : "=r"(v) : "r"(a) : "memory"); return v; }
__device__ __forceinline__ uint4 lds_u4(uint32_t a) {
    uint4 v;
    asm volatile("ld.shared.v4.b32 {%0,%1,%2,%3}, [%4];" : "=r"(v.x), "=r"(v.y), "=r"(v.z), "=r"(v.w) : "r"(a) : "memory");
    return v;
}
__device__ __forceinline__ float4 lds_f4(uint32_t a) {
    float4 v;
    asm volatile("ld.shared.v4.f32 {%0,%1,%2,%3}, [%4];" : "=f"(v.x), "=f"(v.y), "=f"(v.z), "=f"(v.w) : "r"(a) : "memory");
    return v;
}
__device__ __forceinline__ float lds_bf(uint32_t a) {
    uint16_t v;
    asm volatile("ld.shared.b16 %0, [%1];" : "=h"(v) : "r"(a) : "memory");
    return __uint_as_float((uint32_t)v << 16);
}
__device__ __forceinline__ void sts_f(uint32_t a, float v) { asm volatile("st.shared.f32 [%0], %1;" ::"r"(a), "f"(v) : "memory"); }
__device__ __forceinline__ void sts_u(uint32_t a, uint32_t v) { asm volatile("st.shared.b32 [%0], %1;" ::"r"(a), "r"(v) : "memory"); }
__device__ __forceinline__ void sts_bf(uint32_t a, float v) {
    asm volatile("st.shared.b16 [%0], %1;" ::"r"(a), "h"((uint16_t)bf16bits(v)) : "memory");
}
__device__ __forceinline__ void expect_tx(uint32_t bar, uint32_t bytes) {
    asm volatile("mbarrier.arrive.expect_tx.shared::cta.b64 _, [%0], %1;" ::"r"(bar), "r"(bytes) : "memory");
}
__device__ __forceinline__ void bulk_copy(uint32_t dst, const void* src, uint32_t bytes, uint32_t bar) {
    asm volatile("cp.async.bulk.shared::cluster.global.mbarrier::complete_tx::bytes [%0], [%1], %2, [%3];"
                 ::"r"(dst), "l"(src), "r"(bytes), "r"(bar) : "memory");
}
__device__ __forceinline__ void bulk_stream(uint32_t dst, const void* src, uint32_t bytes, uint32_t bar, uint64_t pol) {
    asm volatile("cp.async.bulk.shared::cluster.global.mbarrier::complete_tx::bytes.L2::cache_hint [%0], [%1], %2, [%3], %4;"
                 ::"r"(dst), "l"(src), "r"(bytes), "r"(bar), "l"(pol) : "memory");
}
__device__ __forceinline__ void tensor_stream(uint32_t dst, const CUtensorMap* tm, int c0, int c1, uint32_t bar, uint64_t pol) {
    asm volatile("cp.async.bulk.tensor.2d.shared::cluster.global.mbarrier::complete_tx::bytes.L2::cache_hint [%0], [%1, {%2, %3}], [%4], %5;"
                 ::"r"(dst), "l"(tm), "r"(c0), "r"(c1), "r"(bar), "l"(pol) : "memory");
}
__device__ __forceinline__ void tensor_stream_groups(uint32_t dst, const CUtensorMap* tm, int row, int group, uint32_t bar, uint64_t pol) {
    asm volatile("cp.async.bulk.tensor.3d.shared::cluster.global.mbarrier::complete_tx::bytes.L2::cache_hint [%0], [%1, {%2, %3, %4}], [%5], %6;"
                 ::"r"(dst), "l"(tm), "r"(0), "r"(row), "r"(group), "r"(bar), "l"(pol) : "memory");
}
__device__ __forceinline__ void prefetch_map(const CUtensorMap* tm) { asm volatile("prefetch.tensormap [%0];" ::"l"(tm) : "memory"); }
__device__ __forceinline__ uint32_t timer_ns() { uint32_t t; asm volatile("mov.u32 %0, %%globaltimer_lo;" : "=r"(t)); return t; }
__device__ __forceinline__ void pace(uint32_t t0, int dt) {
#pragma unroll 1
    for (int it = 0; (int)(timer_ns() - t0) < dt && it < (1 << 14); it++) {}
}
__device__ __forceinline__ uint32_t next_epoch(uint32_t e) { return e + 1 < 3u * 65536u ? e + 1 : 0u; }
__device__ __forceinline__ uint32_t tagged(float v, uint32_t tag) { return (__float_as_uint(v) & ~3u) | tag; }
__device__ __forceinline__ bool has_tag(uint32_t v, uint32_t tag) { return ((v ^ tag) & 3u) == 0; }
__device__ __forceinline__ void fold_group(const float (*c)[4], float& r0, float& r1) {
    float t[8];
#pragma unroll
    for (int k = 0; k < 4; k++) {
        t[2 * k] = c[k][0] + c[k][3];
        t[2 * k + 1] = c[k][1] + c[k][2];
    }
    const float a0 = t[0] + __shfl_xor_sync(0xffffffffu, t[2], 1), a1 = t[1] + __shfl_xor_sync(0xffffffffu, t[3], 1);
    const float b0 = t[4] + __shfl_xor_sync(0xffffffffu, t[6], 1), b1 = t[5] + __shfl_xor_sync(0xffffffffu, t[7], 1);
    r0 = a0 + __shfl_xor_sync(0xffffffffu, b0, 2);
    r1 = a1 + __shfl_xor_sync(0xffffffffu, b1, 2);
}
template <typename T>
__device__ __forceinline__ T* pinned(T* p, int lane) {
    return (T*)__shfl_sync(0xffffffffu, (unsigned long long)p, lane);
}

constexpr float FIX_SCALE = 268435456.f, FIX_LIMIT = 16384.f;
constexpr unsigned long long SIDE_ARRIVAL = 129;
__device__ __forceinline__ int acc_index(int col) {
    col = (col & ~63) | ((col & 8) << 2) | ((col & 48) >> 1) | (col & 7);
    return ACC_OFF + (col >> 4 & 1) * ACC_PAIR + (col >> 5) * ACC_STEP + (col & 15);
}
__device__ __forceinline__ void fix_words(float v0, float v1, unsigned long long& w0, unsigned long long& w1) {
    constexpr uint32_t MAGIC = 0x4B400000u;
    asm volatile(
        "{\n.reg .pred p;\n.reg .f32 a0, a1, b0, b1, r0, r1;\n.reg .b32 k0, k1, i0, i1, one, lo, hi;\n"
        "abs.f32 r0, %2;\nabs.f32 r1, %3;\nsetp.lt.f32 p, r0, %4;\nsetp.lt.and.f32 p, r1, %4, p;\n"
        "fma.rn.f32 a0, %2, 0f43800000, 0f4B400000;\nfma.rn.f32 a1, %3, 0f43800000, 0f4B400000;\n"
        "sub.rn.f32 r0, a0, 0f4B400000;\nsub.rn.f32 r1, a1, 0f4B400000;\n"
        "fma.rn.f32 r0, r0, 0fBB800000, %2;\nfma.rn.f32 r1, r1, 0fBB800000, %3;\n"
        "mov.f32 b0, 0f00000000;\nmov.f32 b1, 0f00000000;\nmov.b32 k0, 0;\nmov.b32 k1, 0;\n"
        "@p fma.rn.f32 b0, r0, %5, 0f4B400000;\n@p fma.rn.f32 b1, r1, %5, 0f4B400000;\n"
        "mov.b32 i0, a0;\nmov.b32 i1, a1;\n@p mad.lo.u32 k0, i0, 4, %6;\n@p mad.lo.u32 k1, i1, 4, %6;\n"
        "selp.b32 one, 1, 0, p;\nmov.b32 i0, b0;\nmov.b32 i1, b1;\n"
        "mad.lo.u32 lo, i0, 16384, one;\nmad.hi.u32 hi, i0, 16384, k0;\nmov.b64 %0, {lo, hi};\n"
        "mad.lo.u32 lo, i1, 16384, one;\nmad.hi.u32 hi, i1, 16384, k1;\nmov.b64 %1, {lo, hi};\n}"
        : "=l"(w0), "=l"(w1) : "f"(v0), "f"(v1), "f"(FIX_LIMIT), "f"(FIX_SCALE), "n"(0u - (MAGIC * 4u + (MAGIC >> 18))));
}
__device__ __forceinline__ float fix_value(unsigned long long t) {
    constexpr float ULP = 1.0f / (16384.f * FIX_SCALE);
    return fmaf((float)(int)(t >> 32), 262144.f / FIX_SCALE, fmaf((float)(uint32_t)t, ULP, -NS * ULP));
}
__device__ __forceinline__ unsigned long long atom_add(unsigned long long* p, unsigned long long v) {
    unsigned long long old;
    asm volatile("atom.relaxed.gpu.global.add.u64 %0, [%1], %2;" : "=l"(old) : "l"(p), "l"(v) : "memory");
    return old;
}
__device__ __forceinline__ uint32_t gated_sum(float s0, float s1, uint32_t g, uint32_t x) {
    uint32_t u;
    asm("{\n.reg .b32 t;\ncvt.rn.bf16x2.f32 t, %2, %1;\nmul.rn.bf16x2 t, t, %3;\nadd.rn.bf16x2 %0, %4, t;\n}"
        : "=r"(u) : "f"(s0), "f"(s1), "r"(g), "r"(x));
    return u;
}
__device__ __forceinline__ void store_if(bool ok, uint16_t* p, uint32_t v) {
    asm volatile("{\n.reg .pred p;\nsetp.ne.b32 p, %2, 0;\n@p st.global.b16 [%0], %1;\n}" ::"l"(p), "h"((uint16_t)v), "r"((int)ok) : "memory");
}
__device__ __forceinline__ void st_rlx_if(bool ok, void* p, uint32_t v) {
    asm volatile("{\n.reg .pred p;\nsetp.ne.b32 p, %2, 0;\n@p st.relaxed.gpu.global.b32 [%0], %1;\n}" ::"l"(p), "r"(v), "r"((int)ok) : "memory");
}
__device__ __forceinline__ void exit_if(bool ok) {
    asm volatile("{\n.reg .pred p;\nsetp.ne.b32 p, %0, 0;\n@p exit;\n}" ::"r"((int)ok) : "memory");
}

__global__ void __launch_bounds__(NTHREADS, 1)
fused_decode_kernel(const __nv_bfloat16* __restrict__ kc, const __nv_bfloat16* __restrict__ x, Scratch* __restrict__ g,
                    __nv_bfloat16* __restrict__ out, const __grid_constant__ CUtensorMap tm_wq,
                    const __grid_constant__ CUtensorMap tm_wd, const __grid_constant__ CUtensorMap tm_wg,
                    const __grid_constant__ CUtensorMap tm_wu, const __grid_constant__ CUtensorMap tm_v,
                    const __grid_constant__ CUtensorMap tm_wo, const __grid_constant__ CUtensorMap tm_wl) {
    extern __shared__ __align__(1024) unsigned char smem[];
    const int tid = threadIdx.x, warp = tid >> 5, lane = tid & 31;
    asm volatile("{\n.reg .pred p;\nsetp.lt.u32 p, %1, 192;\n@p prefetch.global.L2 [%0];\n}"
                 ::"l"((const char*)kc + (size_t)((blockIdx.x >> 2) * SK + (blockIdx.x & 3) * 64) * (DH * 2) + tid * 128), "r"(tid));

    if (warp == 10) {
        const int head = blockIdx.x >> 2, part = blockIdx.x & 3;
        uint64_t pol = 0;
        const char* kp = (const char*)(kc + ((size_t)head * SK + part * 64) * DH);
        if (lane == 0) {
#pragma unroll
            for (int i = 0; i < KSLOTS; i++) mbar_init(KFULL + 8 * i, 1);
            mbar_init(XBAR, 1);
            mbar_init_fence();
            asm volatile("createpolicy.fractional.L2::evict_first.b64 %0, 1.0;" : "=l"(pol));
            expect_tx(KFULL + 8 * POS_K, KSLOT_BYTES);
            bulk_stream(SM_RING + POS_K * KSLOT_BYTES, kp, KSLOT_BYTES, KFULL + 8 * POS_K, pol);
            prefetch_map(&tm_wq);
            expect_tx(XBAR, D * 2 + 16);
            bulk_copy(SM_X, x, D * 2, XBAR);
            bulk_copy(SM_X + D * 2, g->epoch, 16, XBAR);
        }
        __syncwarp();
        bar_arrive(6, NTHREADS);
        if (lane == 0) {
            expect_tx(KFULL, 2 * WQ_BOX);
            tensor_stream(SM_RING, &tm_wq, head * DH, part * P1_ROWS, KFULL, pol);
            tensor_stream(SM_RING + WQ_BOX, &tm_wq, head * DH, part * P1_ROWS + 32, KFULL, pol);
#pragma unroll
            for (int i = 1; i < POS_K; i++) {
                expect_tx(KFULL + 8 * i, WQ_BOX);
                tensor_stream(SM_RING + i * KSLOT_BYTES, &tm_wq, head * DH, part * P1_ROWS + 32 * (i + 1), KFULL + 8 * i, pol);
            }
            prefetch_map(part < 3 ? &tm_v : &tm_wg);
            prefetch_map(part < 3 ? &tm_wo : &tm_wu);
            prefetch_map(part < 3 ? &tm_wl : &tm_wd);
        }
        __syncwarp();
        bar_sync(7, 64);
        if (lane == 0) {
            const uint32_t t0 = timer_ns() - T_START;
            uint64_t pol_shared;
            asm volatile("createpolicy.fractional.L2::evict_normal.b64 %0, 1.0;" : "=l"(pol_shared));
#pragma unroll 1
            for (int i = POS_K + 1; i < NPOS1; i++) {
                const int s = i & (KSLOTS - 1);
                if (i >= KSLOTS) mbar_wait(KEMPTY + 8 * s, ((i >> 3) - 1) & 1);
                const int pi = i == POS_K + 1 ? 0 : i - DEPTH;
                mbar_wait(KFULL + 8 * (pi & (KSLOTS - 1)), (pi >> 3) & 1);
                pace(t0, T_K0 + T_K * (i - POS_K));
                expect_tx(KFULL + 8 * s, KSLOT_BYTES);
                bulk_stream(SM_RING + s * KSLOT_BYTES, kp + (size_t)(i - POS_K) * PARTS * KSLOT_BYTES, KSLOT_BYTES, KFULL + 8 * s, pol);
            }
            const int ntile = part < 3 ? NVT : head < NFFN ? 6 : 0, n2 = part < 3 || head >= HEAD_D0 ? ntile + 4 : ntile;
            int s = VSLOT0;
#pragma unroll 1
            for (int v = 0; v < n2; v++) {
                if (v < VSLOTS) {
                    const int k0 = s * 4 / 3;
                    mbar_wait(KEMPTY + 8 * k0, k0 >> 2);
                    mbar_wait(KEMPTY + 8 * k0 + 8, k0 >> 2);
                } else {
                    mbar_wait(VEMPTY + 8 * s, (v / VSLOTS - 1) & 1);
                }
                const int pv = v - (part == 3 ? DEPTH_F : DEPTH);
                if (pv >= 0) mbar_wait(VFULL + 8 * ((pv + VSLOT0) % VSLOTS), (pv / VSLOTS) & 1);
                else mbar_wait(KFULL + 8 * ((NPOS1 + pv) & (KSLOTS - 1)), ((NPOS1 + pv) >> 3) & 1);
                if (part < 3) pace(t0, T_V0 + (v < NVT ? T_V * v : T_V * (NVT - 1) + T_WO * (v - NVT + 1)));
                else if (v >= ntile) pace(t0, T_WD0 + T_WD * (v - ntile));
                const uint32_t full = VFULL + 8 * s, dst = SM_RING + s * VSLOT_BYTES;
                if (v >= ntile && part == 3) {
                    const int j = v - ntile;
                    expect_tx(full, DBOX);
                    tensor_stream(dst, &tm_wd, (head - HEAD_D0) * DCOLS, 2 * j * DROWS, full, pol_shared);
                    expect_tx(SFULL + 8 * j, DBOX);
                    tensor_stream(dst + DBOX, &tm_wd, (head - HEAD_D0) * DCOLS, (2 * j + 1) * DROWS, SFULL + 8 * j, pol_shared);
                } else if (v >= ntile) {
                    const int row = head * DH + part * CW + (v - ntile) * 16;
                    if (v < n2 - 1) {
                        expect_tx(full, WO_BLK);
                        tensor_stream_groups(dst, &tm_wo, row, 0, full, pol);
                    } else {
#pragma unroll
                        for (int i = 0; i < WO_PIECES; i++) {
                            const int j = (i + head) % WO_PIECES;
                            expect_tx(LFULL + 8 * j, WO_PIECE);
                            tensor_stream_groups(dst + j * WO_PIECE, &tm_wl, row, 2 * j, LFULL + 8 * j, pol);
                        }
                    }
                } else if (part < 3) {
                    expect_tx(full, VSLOT_BYTES);
                    tensor_stream(dst, &tm_v, part * CW, head * SK + v * 256, full, pol);
                    if (v == GATE_POS) {
                        expect_tx(XBAR, D * 4);
                        bulk_copy(SM_S, g->xg, D * 4, XBAR);
                    }
                    const int st = (v + 1) >> 2;
                    if (v == 0 || ((v & 3) == 3 && st < 4)) {
                        expect_tx(SFULL + 8 * st, 4096);
                        bulk_copy(SM_S + st * 4096, g->xs + head * SK + st * 1024, 4096, SFULL + 8 * st);
                    }
                } else {
                    const int t = v < 3 ? v : v - 3;
                    const CUtensorMap* tm = v < 3 ? &tm_wg : &tm_wu;
                    expect_tx(full, t < 2 ? VSLOT_BYTES : VSLOT_BYTES / 2);
                    tensor_stream(dst, tm, head * CW, t * 256, full, pol);
                    if (t < 2) tensor_stream(dst + VSLOT_BYTES / 2, tm, head * CW, t * 256 + 128, full, pol);
                }
                s = s == VSLOTS - 1 ? 0 : s + 1;
            }
        }
        return;
    }

    const int cta = __shfl_sync(0xffffffffu, (int)blockIdx.x, 0), head = cta >> 2, part = cta & 3;

    const int n = lane >> 2, t4 = lane & 3, n0 = t4 * 2, r8 = lane & 7;
    const bool is_hi = n == n0 + 1, diag = n == n0 || is_hi;
    const int dsh = is_hi ? 16 : 0;
    uint32_t offv[4];
#pragma unroll
    for (int i = 0; i < 4; i++) offv[i] = (uint32_t)(((2 * i + ((lane >> 3) & 1)) ^ r8) * 16);
    const int keyv = r8 + 8 * (lane >> 4);
    const uint32_t red = SM_RED + warp * RED_STRIDE;

    if (warp == 9) {
        if (lane == 0) {
#pragma unroll
            for (int i = 0; i < KSLOTS; i++) mbar_init(KEMPTY + 8 * i, 8);
#pragma unroll
            for (int i = 0; i < VSLOTS; i++) {
                mbar_init(VFULL + 8 * i, 1);
                mbar_init(VEMPTY + 8 * i, 8);
            }
#pragma unroll
            for (int i = 0; i < 4; i++) mbar_init(SFULL + 8 * i, 1);
#pragma unroll
            for (int i = 0; i < WO_PIECES; i++) mbar_init(LFULL + 8 * i, 1);
            mbar_init(OBAR, 2);
            mbar_init_fence();
        }
        __syncwarp();
        bar_arrive(7, 64);
    }
    float* const xq = g->xq + head * PARTS * DH + tid;
    if (warp < 6) st_rlx(xq + part * DH, 0u);
    bar_sync(6, NTHREADS);
    mbar_wait(XBAR, 0);
    const uint32_t epoch = next_epoch(lds_u(SM_X + D * 2));
    const uint32_t tag = epoch % 3u + 1u, tag16 = epoch & 0xffffu;

    float ln_m, ln_d;
    {
        float v[20];
#pragma unroll
        for (int i = 0; i < 10; i++) {
            const uint32_t u = lds_u(SM_X + (lane + 32 * i) * 4);
            v[2 * i] = __uint_as_float(u << 16);
            v[2 * i + 1] = __uint_as_float(u & 0xffff0000u);
        }
        float sum = 0.f, sq = 0.f;
#pragma unroll
        for (int i = 0; i < 20; i++) sum += v[i];
#pragma unroll
        for (int o = 16; o; o >>= 1) sum += __shfl_xor_sync(0xffffffffu, sum, o);
        const float mean = sum * (1.0f / D);
#pragma unroll
        for (int i = 0; i < 20; i++) sq = fmaf(v[i] - mean, v[i] - mean, sq);
#pragma unroll
        for (int o = 16; o; o >>= 1) sq += __shfl_xor_sync(0xffffffffu, sq, o);
        ln_m = bf16r(mean);
        ln_d = bf16r(__fsqrt_rn(bf16r(bf16r(sq * (1.0f / D)) + 1e-5f)));
    }
    auto xn = [&](float xv) -> float { return __fdividef(bf16r(xv - ln_m), ln_d); };

    {
        const uint32_t xr = SM_X + (part * P1_ROWS + warp * 16 + n) * 2;
        const uint32_t b0 = diag ? bf16bits(xn(lds_bf(xr))) << dsh : 0u, b1 = diag ? bf16bits(xn(lds_bf(xr + 16))) << dsh : 0u;
        const int s = warp < 4 ? 0 : (warp >> 1) - 1;
        mbar_wait(KFULL + 8 * s, 0);
        const uint32_t base = SM_RING + s * KSLOT_BYTES + ((warp < 4 ? warp : warp & 1) * 16 + keyv) * (DH * 2);
        float c[12][4];
#pragma unroll
        for (int i = 0; i < 12; i++) {
            uint32_t a[4];
            c[i][0] = c[i][1] = c[i][2] = c[i][3] = 0.f;
            ldsm4t(a, base + (i >> 2) * 128 + offv[i & 3]);
            mma16816(c[i], a, b0, b1);
        }
        __syncwarp();
        if (lane < (warp < 4 ? 2 : 4)) mbar_arrive(KEMPTY + 8 * s);
#pragma unroll
        for (int j = 0; j < 3; j++) {
            float r0, r1;
            fold_group(c + 4 * j, r0, r1);
            sts_f(red + ((j * 8 + n0) * 8 + n) * 4, r0);
            sts_f(red + ((j * 8 + n0 + 1) * 8 + n) * 4, r1);
        }
    }

    const bool gemv = part < 3 || head < NFFN;
    const int n4 = part < 3 ? 320 : 256;
    if (warp < 8) {
        if (warp < 6) {
            bar_sync(1, 320);
            float s = 0.f;
#pragma unroll
            for (int w = 0; w < 10; w++) s += lds_f(SM_RED + w * RED_STRIDE + tid * 4);
            const uint32_t own = tagged(s, tag);
            st_rlx(xq + part * DH, own);
            const uint32_t tg = next_epoch(lds_u(SM_X + D * 2)) % 3u + 1u;
            uint32_t pv[PARTS];
#pragma unroll
            for (int j = 0; j < PARTS; j++) pv[j] = j == part ? own : 0u;
#pragma unroll 1
            for (int it = 0;; it++) {
                if (has_tag(pv[0], tg) && has_tag(pv[1], tg) && has_tag(pv[2], tg) && has_tag(pv[3], tg)) break;
                if (it == SPIN_LIMIT) __trap();
                if (it) __nanosleep(100);
#pragma unroll
                for (int j = 0; j < PARTS; j++)
                    if (!has_tag(pv[j], tg)) pv[j] = ld_rlx(xq + j * DH);
            }
            sts_bf(SM_Q + tid * 2, (__uint_as_float(pv[0]) + __uint_as_float(pv[1])) + (__uint_as_float(pv[2]) + __uint_as_float(pv[3])));
        } else {
            bar_arrive(1, 320);
        }
        bar_sync(2, 256);

        {
            const int grp = warp >> 2;
            uint32_t qb[12][2], offk[4];
#pragma unroll
            for (int i = 0; i < 12; i++)
#pragma unroll
                for (int e = 0; e < 2; e++) qb[i][e] = lds_u(SM_Q + (((i >> 2) * 8 + ((2 * (i & 3) + e) ^ n)) * 8 + n0) * 2);
#pragma unroll
            for (int i = 0; i < 4; i++) offk[i] = (uint32_t)(((2 * i + (lane >> 4)) ^ r8) * 16);
            const uint32_t rowk = SM_RING + ((warp & 3) * 16 + r8 + 8 * ((lane >> 3) & 1)) * (DH * 2);
            uint32_t* xs_out = g->xs + head * SK + (grp * PARTS + part) * 64 + (warp & 3) * 16 + n;
#pragma unroll 1
            for (int u = 0; u < NKT / 2; u++) {
                const int i = POS_K + 2 * u + grp, s = i & (KSLOTS - 1);
                mbar_wait(KFULL + 8 * s, (i >> 3) & 1);
                const uint32_t base = rowk + s * KSLOT_BYTES;
                float c[3][4];
#pragma unroll
                for (int j = 0; j < 3; j++) c[j][0] = c[j][1] = c[j][2] = c[j][3] = 0.f;
#pragma unroll
                for (int k = 0; k < 4; k++)
#pragma unroll
                    for (int j = 0; j < 3; j++) {
                        uint32_t a[4];
                        ldsm4(a, base + j * 128 + offk[k]);
                        mma16816(c[j], a, qb[j * 4 + k][0], qb[j * 4 + k][1]);
                    }
                __syncwarp();
                if (lane < 2) mbar_arrive(KEMPTY + 8 * s);
                const float d0 = is_hi ? c[0][1] + c[1][1] + c[2][1] : c[0][0] + c[1][0] + c[2][0];
                const float d1 = is_hi ? c[0][3] + c[1][3] + c[2][3] : c[0][2] + c[1][2] + c[2][2];
                if (diag) {
                    st_rlx(xs_out, (bf16bits(bf16r(d0) * SCORE_SCALE) << 16) | tag16);
                    st_rlx(xs_out + 8, (bf16bits(bf16r(d1) * SCORE_SCALE) << 16) | tag16);
                }
                xs_out += 2 * PARTS * 64;
            }
        }

        const uint32_t rowv = SM_RING + keyv * 128;
        int s = VSLOT0, ph = 0;
        if (part < 3) {
            float acc[4][4], m = -INFINITY, l = 0.f, scale = 0.f;
#pragma unroll
            for (int k = 0; k < 4; k++) acc[k][0] = acc[k][1] = acc[k][2] = acc[k][3] = 0.f;
            const uint32_t pw = SM_P + warp * 256;
            const uint32_t pst = pw + ((lane >> 3) * 16 + (lane & 1) * 8 + ((lane >> 2) & 1) * 2 + ((lane >> 1) & 1)) * 4;
#pragma unroll 1
            for (int st = 0; st < 4; st++) {
                const int key0 = st * 1024 + (lane >> 3) * 256 + warp * 32 + r8 * 4;
                mbar_wait(SFULL + 8 * st, 0);
                uint4 sc = lds_u4(SM_S + key0 * 4);
#pragma unroll 1
                for (int it = 0;; it++) {
                    if (((((sc.x ^ tag16) | (sc.y ^ tag16)) | ((sc.z ^ tag16) | (sc.w ^ tag16))) & 0xffffu) == 0) break;
                    if (it == SPIN_LIMIT) __trap();
                    if (it) __nanosleep(100);
                    sc = ld_rlx4(g->xs + head * SK + key0);
                }
                const float s0 = __uint_as_float(sc.x & 0xffff0000u), s1 = __uint_as_float(sc.y & 0xffff0000u);
                const float s2 = __uint_as_float(sc.z & 0xffff0000u), s3 = __uint_as_float(sc.w & 0xffff0000u);
                __syncwarp();
                float mn = fmaxf(fmaxf(s0, s1), fmaxf(s2, s3));
#pragma unroll
                for (int o = 16; o; o >>= 1) mn = fmaxf(mn, __shfl_xor_sync(0xffffffffu, mn, o));
                mn = fmaxf(mn, m);
                const float f = exp2f((m - mn) * LOG2E);
                m = mn;
                const float p0 = exp2f((s0 - m) * LOG2E), p1 = exp2f((s1 - m) * LOG2E);
                const float p2 = exp2f((s2 - m) * LOG2E), p3 = exp2f((s3 - m) * LOG2E);
                l = l * f + ((p0 + p1) + (p2 + p3));
#pragma unroll
                for (int k = 0; k < 4; k++) { acc[k][0] *= f; acc[k][2] *= f; }
                sts_u(pst, pack2(p0, p1));
                sts_u(pst + 16, pack2(p2, p3));
                __syncwarp();
                if (st == 3) {
#pragma unroll
                    for (int o = 16; o; o >>= 1) l += __shfl_xor_sync(0xffffffffu, l, o);
                    if (lane == 0) { sts_f(SM_MISC + warp * 4, m); sts_f(SM_MISC + 32 + warp * 4, l); }
                    bar_sync(3, 256);
                    const float mw = lds_f(SM_MISC + r8 * 4), lw = lds_f(SM_MISC + 32 + r8 * 4);
                    float mm = mw;
#pragma unroll
                    for (int o = 4; o; o >>= 1) mm = fmaxf(mm, __shfl_xor_sync(0xffffffffu, mm, o));
                    float ls = lw * exp2f((mw - mm) * LOG2E);
#pragma unroll
                    for (int o = 4; o; o >>= 1) ls += __shfl_xor_sync(0xffffffffu, ls, o);
                    scale = __fdividef(exp2f((m - mm) * LOG2E), ls);
                }
#pragma unroll 1
                for (int u = 0; u < 4; u++) {
                    const uint4 pb = lds_u4(pw + u * 64 + t4 * 16);
                    mbar_wait(VFULL + 8 * s, ph);
                    const uint32_t base = rowv + s * VSLOT_BYTES + warp * 32 * 128;
                    uint32_t a[8][4];
#pragma unroll
                    for (int k = 0; k < 8; k++) ldsm4t(a[k], base + (k >> 2) * 2048 + offv[k & 3]);
#pragma unroll
                    for (int k = 0; k < 8; k++) mma16816(acc[k & 3], a[k], k < 4 ? pb.x : pb.z, k < 4 ? pb.y : pb.w);
                    __syncwarp();
                    if (lane == 0) mbar_arrive(VEMPTY + 8 * s);
                    if (++s == VSLOTS) s = 0;
                    if (s == VSLOT0) ph ^= 1;
                }
            }
            const float o0 = t4 == 0 ? acc[0][0] : t4 == 1 ? acc[1][0] : t4 == 2 ? acc[2][0] : acc[3][0];
            const float o1 = t4 == 0 ? acc[0][2] : t4 == 1 ? acc[1][2] : t4 == 2 ? acc[2][2] : acc[3][2];
            sts_f(SM_RED + ((t4 * 16 + n) * 8 + (warp ^ t4)) * 4, o0 * scale);
            sts_f(SM_RED + ((t4 * 16 + 8 + n) * 8 + (warp ^ t4)) * 4, o1 * scale);
        } else if (gemv) {
#pragma unroll 1
            for (int mat = 0; mat < 2; mat++) {
                float acc[4][4];
#pragma unroll
                for (int k = 0; k < 4; k++) acc[k][0] = acc[k][1] = acc[k][2] = acc[k][3] = 0.f;
#pragma unroll 1
                for (int t = 0; t < 3; t++) {
                    mbar_wait(VFULL + 8 * s, 0);
#pragma unroll 1
                    for (int ks = 0; ks < (t < 2 ? 2 : 1); ks++) {
                        const int row = t < 2 ? warp * 32 + ks * 16 : warp * 16;
                        const uint32_t u0 = lds_u(SM_X + (t * 256 + row + n0) * 2), u1 = lds_u(SM_X + (t * 256 + row + 8 + n0) * 2);
                        const uint32_t b0 = pack2(xn(__uint_as_float(u0 << 16)), xn(__uint_as_float(u0 & 0xffff0000u)));
                        const uint32_t b1 = pack2(xn(__uint_as_float(u1 << 16)), xn(__uint_as_float(u1 & 0xffff0000u)));
#pragma unroll
                        for (int k = 0; k < 4; k++) {
                            uint32_t a[4];
                            ldsm4t(a, rowv + s * VSLOT_BYTES + row * 128 + offv[k]);
                            mma16816(acc[k], a, b0, b1);
                        }
                    }
                    __syncwarp();
                    if (lane == 0) mbar_arrive(VEMPTY + 8 * s);
                    if (++s == VSLOTS) s = 0;
                }
                const float o0 = t4 == 0 ? acc[0][0] : t4 == 1 ? acc[1][0] : t4 == 2 ? acc[2][0] : acc[3][0];
                const float o1 = t4 == 0 ? acc[0][2] : t4 == 1 ? acc[1][2] : t4 == 2 ? acc[2][2] : acc[3][2];
                sts_f(SM_RED + mat * 2048 + ((t4 * 16 + n) * 8 + (warp ^ t4)) * 4, o0);
                sts_f(SM_RED + mat * 2048 + ((t4 * 16 + 8 + n) * 8 + (warp ^ t4)) * 4, o1);
            }
        }
        if (gemv) {
            if (warp < 2) {
                bar_sync(4, n4);
                const float4 a0 = lds_f4(SM_RED + tid * 32), a1 = lds_f4(SM_RED + tid * 32 + 16);
                float r = ((a0.x + a0.y) + (a0.z + a0.w)) + ((a1.x + a1.y) + (a1.z + a1.w));
                if (part == 3) {
                    const float4 u0 = lds_f4(SM_RED + 2048 + tid * 32), u1 = lds_f4(SM_RED + 2048 + tid * 32 + 16);
                    r = bf16r(silu(bf16r(r))) * bf16r(((u0.x + u0.y) + (u0.z + u0.w)) + ((u1.x + u1.y) + (u1.z + u1.w)));
                    st_rlx(g->xh + head * CW + tid, (bf16bits(r) << 16) | tag16);
                } else {
                    sts_bf(SM_O + ((tid >> 1) & 3) * 32 + (tid >> 3) * 4 + (tid & 1) * 2, r);
                    __syncwarp();
                    if (lane == 0) mbar_arrive(OBAR);
                }
            } else {
                bar_arrive(4, n4);
            }
        }
    } else {
        bar_arrive(1, 320);
        if ((uint32_t)__cvta_generic_to_shared(smem) != SB) __trap();
        if (part < 3) bar_sync(4, 320);
    }

    if (part < 3) {
        const uint32_t roww = SM_RING + keyv * 128 + warp * 2048;
        const int col = (warp * 8 + n0) * 8 + n;
        mbar_wait(XBAR, 1);
        uint32_t g0 = lds_u(SM_S + col * 4), g1 = lds_u(SM_S + col * 4 + 32);
#pragma unroll 1
        for (int it = 0; (((g0 ^ tag16) | (g1 ^ tag16)) & 0xffffu) != 0; it++) {
            if (it == SPIN_LIMIT) __trap();
            g0 = ld_rlx(g->xg + col);
            g1 = ld_rlx(g->xg + col + 8);
        }
        __syncwarp();
        const float x0 = lds_bf(SM_X + col * 2), x1 = lds_bf(SM_X + col * 2 + 16);
        const uint32_t gp = __byte_perm(g0, g1, 0x7632), xp = __byte_perm(__float_as_uint(x0), __float_as_uint(x1), 0x7632);
        unsigned long long* const acc = pinned(g->acc + acc_index(col), lane);
        uint16_t* const outp = pinned((uint16_t*)out + col, lane);
        unsigned* const epoch_word = pinned(g->epoch, lane);
        mbar_wait(OBAR, 0);
        const uint4 u0 = lds_u4(SM_O + t4 * 32), u1 = lds_u4(SM_O + t4 * 32 + 16);
        const uint32_t bo[4][2] = {{u0.x, u0.y}, {u0.z, u0.w}, {u1.x, u1.y}, {u1.z, u1.w}};
        float c[4][4];
#pragma unroll
        for (int k = 0; k < 4; k++) c[k][0] = c[k][1] = c[k][2] = c[k][3] = 0.f;
#pragma unroll
        for (int ks = 0; ks < 4; ks++) {
            const int s = (NVT + ks + VSLOT0) % VSLOTS;
            if (ks < 3) mbar_wait(VFULL + 8 * s, ((NVT + ks) / VSLOTS) & 1);
            else mbar_spin(LFULL + 8 * (warp >> 1), 0);
            uint32_t a[4][4];
#pragma unroll
            for (int k = 0; k < 4; k++) ldsm4t(a[k], roww + offv[k] + s * VSLOT_BYTES);
#pragma unroll
            for (int k = 3; k >= 0; k--) mma16816(c[k], a[k], bo[ks][0], bo[ks][1]);
        }
        const float r0 = t4 & 2 ? (t4 & 1 ? c[3][0] : c[2][0]) : (t4 & 1 ? c[1][0] : c[0][0]);
        const float r1 = t4 & 2 ? (t4 & 1 ? c[3][2] : c[2][2]) : (t4 & 1 ? c[1][2] : c[0][2]);
        unsigned long long w0, w1;
        fix_words(r0, r1, w0, w1);
        const bool in_range = (uint32_t)w0 & 1u;
        unsigned long long t0 = atom_add(acc, w0) + w0, t1 = atom_add(acc + ACC_STEP, w1) + w1;
        uint32_t u = gated_sum(fix_value(t0), fix_value(t1), gp, xp);
        store_if(((uint32_t)t0 & 0x3fffu) == NS, outp, u);
        store_if(((uint32_t)t1 & 0x3fffu) == NS, outp + 8, u >> 16);
        st_rlx_if(col == 0 && ((uint32_t)t0 & 0x3fffu) == NS, epoch_word, epoch);
        exit_if(in_range && (((uint32_t)t0 | (uint32_t)t1) & (127u << 7)) == 0);
        if (!in_range) {
            atomicAdd(g->big + col, r0);
            atomicAdd(g->big + col + 8, r1);
            __threadfence();
            t0 = atom_add(acc, SIDE_ARRIVAL) + SIDE_ARRIVAL;
            t1 = atom_add(acc + ACC_STEP, SIDE_ARRIVAL) + SIDE_ARRIVAL;
        }
        __threadfence();
        u = gated_sum(fix_value(t0) + __uint_as_float(ld_rlx(g->big + col)), fix_value(t1) + __uint_as_float(ld_rlx(g->big + col + 8)), gp, xp);
        store_if(((uint32_t)t0 & 127u) == NS, outp, u);
        store_if(((uint32_t)t1 & 127u) == NS, outp + 8, u >> 16);
        st_rlx_if(col == 0 && ((uint32_t)t0 & 127u) == NS, epoch_word, epoch);
    }

    if (part == 3 && head >= HEAD_D0) {
        if (warp < 6) {
            const uint32_t* src = g->xh + tid * 8;
            uint4 h0, h1;
#pragma unroll 1
            for (int it = 0;; it++) {
                h0 = ld_rlx4(src);
                h1 = ld_rlx4(src + 4);
                const uint32_t bad = ((h0.x ^ tag16) | (h0.y ^ tag16)) | ((h0.z ^ tag16) | (h0.w ^ tag16)) |
                                     ((h1.x ^ tag16) | (h1.y ^ tag16)) | ((h1.z ^ tag16) | (h1.w ^ tag16));
                if ((bad & 0xffffu) == 0) break;
                if (it == SPIN_LIMIT) __trap();
                __nanosleep(500);
            }
            const uint32_t hs = SM_S + (tid >> 2) * 64 + (tid & 3) * 4;
            sts_u(hs, __byte_perm(h0.x, h0.y, 0x7632));
            sts_u(hs + 16, __byte_perm(h0.z, h0.w, 0x7632));
            sts_u(hs + 32, __byte_perm(h1.x, h1.y, 0x7632));
            sts_u(hs + 48, __byte_perm(h1.z, h1.w, 0x7632));
            bar_sync(3, 192);
            uint4 hb[8];
#pragma unroll
            for (int b = 0; b < 8; b++) hb[b] = lds_u4(SM_S + (b * 6 + warp) * 64 + t4 * 16);
            const uint32_t ph = head < NFFN ? 1 : 0;
            const uint32_t rowd = SM_RING + (warp * 32 + keyv) * 64;
            const uint32_t c0 = (((lane >> 3) & 1) ^ (r8 >> 1)) * 16, c1 = c0 ^ 32;
            float c[4][4];
#pragma unroll
            for (int k = 0; k < 4; k++) c[k][0] = c[k][1] = c[k][2] = c[k][3] = 0.f;
            uint32_t a[2][4][4];
#pragma unroll
            for (int b = 0; b <= 8; b++) {
                if (b < 8) {
                    const int s = (VSLOT0 + (b >> 1)) % VSLOTS;
                    if (b & 1) mbar_wait(SFULL + 8 * (b >> 1), 0);
                    else mbar_wait(VFULL + 8 * s, ph);
                    const uint32_t base = rowd + s * VSLOT_BYTES + (b & 1) * DBOX;
                    ldsm4t(a[b & 1][0], base + c0);
                    ldsm4t(a[b & 1][1], base + c1);
                    ldsm4t(a[b & 1][2], base + 1024 + c0);
                    ldsm4t(a[b & 1][3], base + 1024 + c1);
                }
                if (b > 0) {
                    const uint4 hv = hb[b - 1];
                    mma16816(c[0], a[~b & 1][0], hv.x, hv.y);
                    mma16816(c[1], a[~b & 1][1], hv.x, hv.y);
                    mma16816(c[2], a[~b & 1][2], hv.z, hv.w);
                    mma16816(c[3], a[~b & 1][3], hv.z, hv.w);
                }
            }
            const float f = t4 == 0 ? c[0][0] + c[2][0] : t4 == 1 ? c[0][2] + c[2][2] : t4 == 2 ? c[1][0] + c[3][0] : c[1][2] + c[3][2];
            sts_f(SM_P + warp * 128 + (t4 * 8 + n) * 4, f);
            bar_arrive(5, 224);
        } else if (warp == 8) {
            const int col = (head - HEAD_D0) * DCOLS + lane;
            asm volatile("st.relaxed.gpu.global.u64 [%0], %1;" ::"l"(g->acc + acc_index(col)), "l"(0ull) : "memory");
            st_rlx(g->big + col, 0u);
            __threadfence();
            bar_sync(5, 224);
            float t = 0.f;
#pragma unroll
            for (int w = 0; w < 6; w++) t += lds_f(SM_P + w * 128 + lane * 4);
            st_rlx(g->xg + col, (bf16bits(silu(bf16r(t))) << 16) | tag16);
        }
    }
}

typedef CUresult (*EncodeFn)(CUtensorMap*, CUtensorMapDataType, cuuint32_t, void*, const cuuint64_t*, const cuuint64_t*,
                             const cuuint32_t*, const cuuint32_t*, CUtensorMapInterleave, CUtensorMapSwizzle,
                             CUtensorMapL2promotion, CUtensorMapFloatOOBfill);

void encode_map(EncodeFn fn, CUtensorMap* tm, void* base, int cols, int rows, int box_cols, int box_rows,
                CUtensorMapSwizzle swz, int groups = 1, int box_groups = 1) {
    const cuuint64_t dims[3] = {(cuuint64_t)(cols / groups), (cuuint64_t)rows, (cuuint64_t)groups};
    const cuuint64_t strides[2] = {(cuuint64_t)cols * 2, (cuuint64_t)(cols / groups) * 2};
    const cuuint32_t box[3] = {(cuuint32_t)box_cols, (cuuint32_t)box_rows, (cuuint32_t)box_groups};
    const cuuint32_t estr[3] = {1, 1, 1};
    fn(tm, CU_TENSOR_MAP_DATA_TYPE_BFLOAT16, groups > 1 ? 3 : 2, base, dims, strides, box, estr, CU_TENSOR_MAP_INTERLEAVE_NONE,
       swz, CU_TENSOR_MAP_L2_PROMOTION_L2_128B, CU_TENSOR_MAP_FLOAT_OOB_FILL_NONE);
}

}

extern "C" void kernel_launch(void* const* d_in, const int* in_sizes, int n_in, void* d_out, int out_size) {
    static EncodeFn encode = nullptr;
    static Scratch* scratch = nullptr;
    if (!encode) {
        cudaDriverEntryPointQueryResult qr;
        cudaGetDriverEntryPoint("cuTensorMapEncodeTiled", (void**)&encode, cudaEnableDefault, &qr);
        void* raw;
        cudaGetSymbolAddress(&raw, g_scratch);
        scratch = (Scratch*)(((uintptr_t)raw + SCRATCH_ALIGN - 1) & ~(uintptr_t)(SCRATCH_ALIGN - 1));
        cudaFuncSetAttribute(fused_decode_kernel, cudaFuncAttributeMaxDynamicSharedMemorySize, SMEM_BYTES);
    }
    CUtensorMap tm_wq, tm_wd, tm_wg, tm_wu, tm_v, tm_wo, tm_wl;
    encode_map(encode, &tm_wq, d_in[3], H * DH, D, DH, 32, CU_TENSOR_MAP_SWIZZLE_NONE);
    encode_map(encode, &tm_wd, d_in[8], D, F, DCOLS, DROWS, CU_TENSOR_MAP_SWIZZLE_64B);
    encode_map(encode, &tm_wg, d_in[6], F, D, CW, 128, CU_TENSOR_MAP_SWIZZLE_128B);
    encode_map(encode, &tm_wu, d_in[7], F, D, CW, 128, CU_TENSOR_MAP_SWIZZLE_128B);
    encode_map(encode, &tm_v, d_in[2], DH, H * SK, CW, 256, CU_TENSOR_MAP_SWIZZLE_128B);
    encode_map(encode, &tm_wo, d_in[4], D, H * DH, CW, 16, CU_TENSOR_MAP_SWIZZLE_128B, D / CW, D / CW);
    encode_map(encode, &tm_wl, d_in[4], D, H * DH, CW, 16, CU_TENSOR_MAP_SWIZZLE_128B, D / CW, 2);
    fused_decode_kernel<<<NCTA, NTHREADS, SMEM_BYTES, cudaStreamPerThread>>>(
        (const __nv_bfloat16*)d_in[1], (const __nv_bfloat16*)d_in[0], scratch, (__nv_bfloat16*)d_out, tm_wq, tm_wd, tm_wg,
        tm_wu, tm_v, tm_wo, tm_wl);
}
```
